```python
import torch

def _softmax(x, axis=-1):
    return torch.softmax(x, dim=axis)
def _gelu(x):
    return torch.nn.functional.gelu(x, approximate="tanh")
def _silu(x):
    return torch.nn.functional.silu(x)
def _sigmoid(x):
    return torch.sigmoid(x)
def _layernorm(x, axis=-1, eps=1e-5):
    m = x.mean(dim=axis, keepdim=True)
    v = x.var(dim=axis, keepdim=True, unbiased=False)
    return (x - m) / torch.sqrt(v + eps)
def _scatter_add(tgt, idx, src, axis=0):
    return tgt.clone().index_add_(axis, idx, src)
def _segment_sum(src, seg, n):
    out = torch.zeros((n,) + src.shape[1:], dtype=src.dtype)
    return out.index_add_(0, seg, src)
def _pad(x, pw):
    flat = tuple(v for pair in reversed(pw) for v in pair)
    return torch.nn.functional.pad(x, flat)

kernel_name = 'standalone__winograd__vision'

def setup_inputs():

    _w = (lambda a: (lambda t: t.to(torch.bfloat16) if t.is_floating_point() else t)(torch.as_tensor(a)))
    H = W = 512 // 2 * 2
    C = 192
    return {
        "x": _w((lambda *s: torch.randn(*s, dtype=torch.bfloat16) * 0.05)(1, H, W, C)),
        "w": _w((lambda *s: torch.randn(*s, dtype=torch.bfloat16) * 0.05)(3, 3, C, C)),
    }

def reference(x, w):
    N, H, W, C = x.shape
    K = w.shape[-1]
    G  = torch.as_tensor([[1.0,0.0,0.0],[0.5,0.5,0.5],[0.5,-0.5,0.5],[0.0,0.0,1.0]], dtype=x.dtype)
    Bt = torch.as_tensor([[1.0,0.0,-1.0,0.0],[0.0,1.0,1.0,0.0],[0.0,-1.0,1.0,0.0],[0.0,1.0,0.0,-1.0]], dtype=x.dtype)
    At = torch.as_tensor([[1.0,1.0,1.0,0.0],[0.0,1.0,-1.0,-1.0]], dtype=x.dtype)
    U = torch.einsum("ar,rsck,bs->abck", G, w, G)
    xp = _pad(x, ((0,0),(1,1),(1,1),(0,0)))
    nH, nW = H // 2, W // 2
    patches = []
    for i in range(4):
        for j in range(4):
            patches.append(xp[:, i:i + 2 * nH:2, j:j + 2 * nW:2, :])
    d = torch.stack(patches).reshape(4, 4, N * nH * nW, C)
    V = torch.einsum("ai,ijpc,bj->abpc", Bt, d, Bt)
    M = torch.einsum("abck,abpc->abpk", U, V)
    Y = torch.einsum("ma,abpk,nb->pmnk", At, M, At)
    Y = Y.reshape(N, nH, nW, 2, 2, K)
    Y = (lambda x, *d: x.permute(*d))(Y, 0, 1, 3, 2, 4, 5).reshape(N, H, W, K)
    return Y
```

```cpp
#include <cuda_runtime.h>
#include <cuda_bf16.h>
#include <cuda.h>
#include <stdint.h>

namespace {

constexpr int IMG = 512, CH = 192;
constexpr float PA = 0.6875f, PB = 1.5f;
constexpr float A2 = PA * PA, B2 = PB * PB, DD = B2 - A2;

constexpr int NSTEP = 72, NSUB = 12;
__host__ __device__ constexpr int sched(int i) {
  constexpr int t[NSTEP] = {0x00, 0x10, 0x40, 0x01, 0x11, 0x41, 0x02, 0x42, 0x50, 0x51, 0x52, 0x12, 0x20, 0x21, 0x30, 0x31, 0x22, 0x32, 0x23, 0x33, 0x03, 0x13, 0x24, 0x34, 0x04, 0x14, 0x25, 0x35, 0x05, 0x15, 0x26, 0x36, 0x06, 0x16, 0x27, 0x37, 0x07, 0x17, 0x28, 0x38, 0x08, 0x18, 0x29, 0x39, 0x09, 0x19, 0x2a, 0x3a, 0x0a, 0x1a, 0x2b, 0x3b, 0x1b, 0x0b, 0x43, 0x44, 0x53, 0x45, 0x46, 0x47, 0x48, 0x49, 0x4a, 0x4b, 0x54, 0x55, 0x56, 0x57, 0x58, 0x59, 0x5a, 0x5b};
  return t[i];
}
constexpr int PIV1 = 9, PIV2 = 51;
__host__ __device__ constexpr int step_p(int i) { return sched(i) >> 4; }
__host__ __device__ constexpr int step_n(int i) { return sched(i) & 15; }
__host__ __device__ constexpr int step_acc(int i) { return step_p(i) < 4 ? step_p(i) : step_p(i) - 2; }
__host__ __device__ constexpr int first_on(int acc) {
  for (int i = 0; i < NSTEP; i++)
    if (step_acc(i) == acc) return i;
  return -1;
}
__host__ __device__ constexpr int last_on(int acc) {
  for (int i = NSTEP - 1; i >= 0; i--)
    if (step_acc(i) == acc) return i;
  return -1;
}
__host__ __device__ constexpr int find_step(int p, int n) {
  for (int i = 0; i < NSTEP; i++)
    if (sched(i) == p * 16 + n) return i;
  return -1;
}
__host__ __device__ constexpr int first_use(int n) {
  for (int i = 0; i < NSTEP; i++)
    if (step_n(i) == n) return i;
  return -1;
}
constexpr float S1 = 1.f / PA, S2 = 1.f / (2.f * A2);
constexpr float S3_Z0 = 0.5f, S3_B = S3_Z0 * (-A2 / DD);
constexpr float S4_I0 = 2.f, S4_B = S4_I0 * (-1.f / (2.f * PB * DD));

constexpr int NV = 31, NB = 6;
__host__ __device__ constexpr int vslot(int p, int n) {
  constexpr int t[6][NSUB] = {{26, 15, 0, 23, 11, 19, 26, 28, 22, 25, 14, 19}, {29, 21, 2, 13, 22, 10, 27, 17, 30, 27, 15, 20}, {25, 20, 19, 28, 12, 25, 21, 16, 19, 29, 28, 21}, {30, 14, 4, 26, 15, 29, 20, 14, 24, 26, 16, 22}, {27, 16, 1, 0, 2, 4, 6, 8, 10, 12, 17, 23}, {28, 22, 6, 1, 3, 5, 7, 9, 11, 13, 18, 24}};
  return t[p][n];
}
__host__ __device__ constexpr int gate(int n) {
  constexpr int t[NSUB] = {-26, -20, -14, 8, 13, 17, 21, 25, 29, 33, 37, 41};
  return t[n];
}
__host__ __device__ constexpr int gate_of(int i) {
  for (int n = 0; n < NSUB; n++)
    if ((gate(n) + NSTEP) % NSTEP == i) return n;
  return -1;
}
__host__ __device__ constexpr bool gates_ok() {
  for (int n = 0; n < NSUB; n++) {
    for (int p = 0; p < 6; p++)
      for (int d = 1; d <= NSUB; d++)
        for (int q = 0; q < 6; q++) {
          const int m = (n - d + NSUB) % NSUB;
          if (vslot(q, m) == vslot(p, n) && (find_step(q, m) - (n - d < 0 ? NSTEP : 0) > gate(n) || (m == n && p != q))) return false;
        }
    if (n > 0 && (gate(n) <= gate(n - 1) || first_use(n) <= first_use(n - 1))) return false;
    if (gate(n) >= first_use(n)) return false;
    if (gate((n + NB) % NSUB) + (n >= NB ? NSTEP : 0) < first_use(n)) return false;
  }
  return gate(0) + NSTEP > gate(NSUB - 1) && gate(NB) >= 0;
}
static_assert(gates_ok(), "gates");

constexpr int UTILE = CH * 16 * 2;
constexpr int USLAB = 3 * UTILE;
constexpr int NU = 4;
constexpr int VROW = 66 * 16;
constexpr int VPIECE = 2 * VROW;
constexpr int VSLOT = 2 * VPIECE;
constexpr int XBOX = 10 * 8 * 32;
static_assert(NSTEP % (2 * NU) == 0, "static ring parity");

constexpr int OFF_X = 0;
constexpr int OFF_U = OFF_X + 9 * XBOX;
constexpr int OFF_V = OFF_U + NU * USLAB;
constexpr int OFF_BAR = OFF_V + NV * VSLOT;
constexpr int BAR_UFULL = OFF_BAR;
constexpr int BAR_UEMPTY = BAR_UFULL + 8 * NU;
constexpr int BAR_XFULL = BAR_UEMPTY + 8 * NU;
constexpr int BAR_VFULL = BAR_XFULL + 8 * 9;
constexpr int BAR_GATE = BAR_VFULL + 8 * NB;
constexpr int OFF_OSC = BAR_GATE + 8 * NB;
constexpr int BAR_DUMMY = OFF_OSC + 8;
constexpr int OFF_DUMMY = (BAR_DUMMY + 8 + 127) / 128 * 128;
constexpr int SMEM_BYTES = OFF_DUMMY + (7 >= 7 ? 768 : 128);
constexpr uint32_t SMEM_BASE = 1024;
static_assert(SMEM_BYTES <= 232448, "smem");

constexpr int NREG = 512;

__device__ __align__(128) uint4 g_U[NSTEP * USLAB / 16];
__device__ uint32_t g_arrived;

__device__ __forceinline__ uint32_t smem_u32(const void* p) { return (uint32_t)__cvta_generic_to_shared(p); }
__device__ __forceinline__ void mbar_init(uint32_t a, int c) {
  asm volatile("mbarrier.init.shared::cta.b64 [%0], %1;" ::"r"(a), "r"(c) : "memory");
}
__device__ __forceinline__ void mbar_arrive(uint32_t a) {
  asm volatile("mbarrier.arrive.shared::cta.b64 _, [%0];" ::"r"(a) : "memory");
}
__device__ __forceinline__ void mbar_wait(uint32_t a, uint32_t parity, uint32_t skip = 0) {
  asm volatile(
      "{\n"
      ".reg .pred p;\n"
      ".reg .u32 n;\n"
      "setp.ne.u32 p, %2, 0;\n"
      "@p bra.uni LAB_DONE;\n"
      "mov.u32 n, 0;\n"
      "LAB_WAIT:\n"
      "mbarrier.try_wait.parity.shared::cta.b64 p, [%0], %1;\n"
      "@p bra.uni LAB_DONE;\n"
      "add.u32 n, n, 1;\n"
      "setp.lt.u32 p, n, 4000000;\n"
      "@p bra.uni LAB_WAIT;\n"
      "trap;\n"
      "LAB_DONE:\n"
      "}\n" ::"r"(a), "r"(parity), "r"(skip) : "memory");
}
__device__ __forceinline__ void mbar_wait_short(uint32_t a, uint32_t parity) {
  asm volatile("{\n.reg .pred p;\nLAB_WAIT:\nmbarrier.try_wait.parity.shared::cta.b64 p, [%0], %1;\n@!p bra.uni LAB_WAIT;\n}\n" ::"r"(a),
               "r"(parity) : "memory");
}
__device__ __forceinline__ bool mbar_test(uint32_t a, uint32_t parity) {
  uint32_t ok;
  asm volatile("{\n.reg .pred p;\nmbarrier.test_wait.parity.shared::cta.b64 p, [%1], %2;\nselp.u32 %0, 1, 0, p;\n}\n"
               : "=r"(ok) : "r"(a), "r"(parity) : "memory");
  return ok;
}
__device__ __forceinline__ void fence_async() { asm volatile("fence.proxy.async.shared::cta;" ::: "memory"); }
__device__ __forceinline__ void tma_box_warp(uint32_t dst, const CUtensorMap* tm, uint32_t bar, uint32_t bytes, int c, int x, int y, uint64_t pol = 0x1000000000000000ull) {
  asm volatile(
      "{\n.reg .pred p;\nelect.sync _|p, 0xffffffff;\n"
      "@p mbarrier.arrive.expect_tx.shared::cta.b64 _, [%2], %6;\n"
      "@p cp.async.bulk.tensor.3d.shared::cluster.global.mbarrier::complete_tx::bytes [%0], [%1, {%3, %4, %5}], [%2];\n}\n" ::"r"(dst),
      "l"(tm), "r"(bar), "r"(c), "r"(x), "r"(y), "r"(bytes), "l"(pol) : "memory");
}
__device__ __forceinline__ void tma_prefetch_warp(const CUtensorMap* tm, int c, int x, int y) {
  asm volatile("{\n.reg .pred p;\nelect.sync _|p, 0xffffffff;\n"
               "@p cp.async.bulk.prefetch.tensor.3d.L2.global.tile [%0, {%1, %2, %3}];\n}\n"
               ::"l"(tm), "r"(c), "r"(x), "r"(y), "l"(0x12F0000000000000ull) : "memory");
}
__device__ __forceinline__ void load_u_warp(uint32_t dst, const void* src, uint32_t bar) {
  asm volatile("{\n.reg .pred p;\nelect.sync _|p, 0xffffffff;\n"
               "@p mbarrier.arrive.expect_tx.shared::cta.b64 _, [%2], %3;\n"
               "@p cp.async.bulk.shared::cluster.global.mbarrier::complete_tx::bytes [%0], [%1], %3, [%2];\n}\n" ::"r"(dst),
               "l"(src), "r"(bar), "n"(USLAB) : "memory");
}
__device__ __forceinline__ uint2 lds64(uint32_t a) {
  uint2 v;
  asm volatile("ld.shared.v2.u32 {%0,%1}, [%2];" : "=r"(v.x), "=r"(v.y) : "r"(a) : "memory");
  return v;
}
__device__ __forceinline__ uint32_t lds32(uint32_t a) {
  uint32_t v;
  asm volatile("ld.shared.u32 %0, [%1];" : "=r"(v) : "r"(a) : "memory");
  return v;
}
__device__ __forceinline__ void sts64(uint32_t a, uint2 v, bool on) {
  if (on) asm volatile("st.shared.v2.u32 [%0], {%1,%2};" ::"r"(a), "r"(v.x), "r"(v.y) : "memory");
}
__device__ __forceinline__ void sched_barrier() { asm volatile("pmevent 0;" ::: "memory"); }
__device__ __forceinline__ void mbar_arrive_cluster(uint32_t a) {
  asm volatile("mbarrier.arrive.shared::cluster.b64 _, [%0];" ::"r"(a) : "memory");
}
__device__ __forceinline__ void spin_cycles(uint32_t n) {
  asm volatile(
      "{\n.reg .pred p;\n.reg .u32 t0, t;\n"
      "mov.u32 t0, %%clock;\n"
      "LAB_SPIN:\n"
      "nanosleep.u32 50;\n"
      "mov.u32 t, %%clock;\nsub.u32 t, t, t0;\nsetp.lt.u32 p, t, %0;\n"
      "@p bra.uni LAB_SPIN;\n}\n" ::"r"(n) : "memory");
}
__device__ __forceinline__ void grid_barrier(uint32_t* ctr, uint32_t n, uint32_t old) {
  asm volatile(
      "{\n.reg .pred p;\n.reg .u32 v, i, inc;\n"
      "setp.eq.u32 p, %2, 0;\n"
      "sub.u32 inc, 0x80000001, %1;\n"
      "selp.u32 inc, inc, 1, p;\n"
      "elect.sync _|p, 0xffffffff;\n"
      "@p red.release.gpu.global.add.u32 [%0], inc;\n"
      "bar.arrive 2, 128;\n"
      "mov.u32 i, 0;\n"
      "LAB_POLL:\n"
      "ld.acquire.gpu.global.u32 v, [%0];\n"
      "xor.b32 v, v, %3;\nsetp.lt.s32 p, v, 0;\n"
      "@p bra.uni LAB_OUT;\n"
      "add.u32 i, i, 1;\nsetp.lt.u32 p, i, 4000000;\n"
      "@p bra.uni LAB_POLL;\n"
      "trap;\n"
      "LAB_OUT:\n}\n" ::"l"(ctr), "r"(n), "r"(blockIdx.x), "r"(old) : "memory");
}
__device__ __forceinline__ void cluster_arrive_relaxed() { asm volatile("barrier.cluster.arrive.relaxed.aligned;" ::: "memory"); }
__device__ __forceinline__ void cluster_wait() { asm volatile("barrier.cluster.wait.acquire.aligned;" ::: "memory"); }

__host__ __device__ constexpr uint32_t h2const(float v) {
  double a = v < 0 ? -v : v;
  int e = 15;
  while (a >= 2) { a /= 2; e++; }
  while (a < 1) { a *= 2; e--; }
  const uint32_t h = (v < 0 ? 0x8000u : 0u) | ((e << 10) + (uint32_t)((a - 1) * 1024 + 0.5));
  return h | h << 16;
}
__device__ __forceinline__ uint32_t hfma2(uint32_t a, uint32_t b, uint32_t c) {
  uint32_t d;
  asm("fma.rn.f16x2 %0, %1, %2, %3;" : "=r"(d) : "r"(a), "r"(b), "r"(c));
  return d;
}
__device__ __forceinline__ uint32_t bmul2(uint32_t a, uint32_t b) {
  uint32_t d;
  asm("mul.rn.bf16x2 %0, %1, %2;" : "=r"(d) : "r"(a), "r"(b));
  return d;
}
__device__ __forceinline__ uint2 fma4(uint32_t k, const uint2& a, const uint2& c) { return make_uint2(hfma2(k, a.x, c.x), hfma2(k, a.y, c.y)); }
__device__ __forceinline__ uint32_t pack_bf16(float lo, float hi) {
  uint32_t d;
  asm("cvt.rn.bf16x2.f32 %0, %1, %2;" : "=r"(d) : "f"(hi), "f"(lo));
  return d;
}
__device__ __forceinline__ uint32_t pack_f16(float lo, float hi) {
  uint32_t d;
  asm("cvt.rn.f16x2.f32 %0, %1, %2;" : "=r"(d) : "f"(hi), "f"(lo));
  return d;
}

template <int AOFF, int BOFF>
__device__ __forceinline__ void wgmma192(uint32_t (&d)[48], uint64_t da, uint64_t db, uint32_t scale_d) {
  asm volatile(
      "{\n.reg .pred p;\n.reg .b64 qa, qb;\n"
      "setp.ne.b32 p, %50, 0;\n"
      "add.s64 qa, %48, %51;\nadd.s64 qb, %49, %52;\n"
      "wgmma.mma_async.sync.aligned.m64n192k16.f16.f16.f16 "
      "{%0, %1, %2, %3, %4, %5, %6, %7, %8, %9, %10, %11, %12, %13, %14, %15, "
      "%16, %17, %18, %19, %20, %21, %22, %23, %24, %25, %26, %27, %28, %29, %30, %31, "
      "%32, %33, %34, %35, %36, %37, %38, %39, %40, %41, %42, %43, %44, %45, %46, %47}, "
      "qa, qb, p, 1, 1, 0, 0;\n}\n"
      : "+r"(d[0]), "+r"(d[1]), "+r"(d[2]), "+r"(d[3]), "+r"(d[4]), "+r"(d[5]), "+r"(d[6]), "+r"(d[7]), "+r"(d[8]),
        "+r"(d[9]), "+r"(d[10]), "+r"(d[11]), "+r"(d[12]), "+r"(d[13]), "+r"(d[14]), "+r"(d[15]), "+r"(d[16]),
        "+r"(d[17]), "+r"(d[18]), "+r"(d[19]), "+r"(d[20]), "+r"(d[21]), "+r"(d[22]), "+r"(d[23]), "+r"(d[24]),
        "+r"(d[25]), "+r"(d[26]), "+r"(d[27]), "+r"(d[28]), "+r"(d[29]), "+r"(d[30]), "+r"(d[31]), "+r"(d[32]),
        "+r"(d[33]), "+r"(d[34]), "+r"(d[35]), "+r"(d[36]), "+r"(d[37]), "+r"(d[38]), "+r"(d[39]), "+r"(d[40]),
        "+r"(d[41]), "+r"(d[42]), "+r"(d[43]), "+r"(d[44]), "+r"(d[45]), "+r"(d[46]), "+r"(d[47])
      : "l"(da), "l"(db), "r"(scale_d), "n"(AOFF >> 4), "n"(BOFF >> 4));
}
__device__ __forceinline__ void wg_fence() { asm volatile("wgmma.fence.sync.aligned;" ::: "memory"); }
__device__ __forceinline__ void wg_commit() { asm volatile("wgmma.commit_group.sync.aligned;" ::: "memory"); }
template <int N>
__device__ __forceinline__ void wg_wait() { asm volatile("wgmma.wait_group.sync.aligned %0;" ::"n"(N) : "memory"); }
__device__ __forceinline__ void reg_fence(uint32_t (&d)[48]) {
#pragma unroll
  for (int i = 0; i < 48; i++) asm volatile("" : "+r"(d[i])::"memory");
}

constexpr uint32_t X_EXP = 17;
constexpr uint32_t X_LIM = ((15 + 8) << 7) - 1;
constexpr uint32_t U_LIM = ((15 + 6) << 10) - 1;
constexpr uint32_t Y_MIN = 0x3C00, Y_INF = 0x7C00;
constexpr uint32_t NAN2 = 0x7FFF7FFFu;
using Sample = uint4;
__device__ __forceinline__ uint4 ldg128(const uint4* p) {
  uint4 v;
  asm volatile("ld.global.v4.u32 {%0,%1,%2,%3}, [%4];" : "=r"(v.x), "=r"(v.y), "=r"(v.z), "=r"(v.w) : "l"(p));
  return v;
}
__device__ __forceinline__ Sample sample_w(const __nv_bfloat16* w, int lane) {
  const int q = lane >> 3;
  return ldg128((const uint4*)(w + ((q == 0 ? 1 : q == 1 ? 3 : 4) * CH + 47 * q) * CH + 64 * (q % 3)) + (lane & 7));
}
__device__ __forceinline__ Sample sample_x(const __nv_bfloat16* x, int r, int lane) {
  return ldg128((const uint4*)(x + (size_t)(((r >> 3) * 8 + 1 + lane % 6) * IMG + (r & 7) * 64 + 2 * lane) * CH) + lane % 24);
}
__device__ __forceinline__ uint32_t sample_exp(const Sample& s) {
  const uint32_t m = __vmaxu2(__vimax3_u16x2(s.x & NAN2, s.y & NAN2, s.z & NAN2), s.w & NAN2);
  return __reduce_max_sync(0xffffffffu, max(m & 0xFFFFu, m >> 16)) >> 7;
}

constexpr int NPREP = 3 * 24 * CH;
__host__ __device__ constexpr int early(int p) {
  int c = 0;
  while (find_step(p, c) < PIV2) c++;
  return c;
}
__device__ __forceinline__ float ldg_bf16(const __nv_bfloat16* p) {
  uint16_t v;
  asm volatile("ld.global.nc.u16 %0, [%1];" : "=h"(v) : "l"(p));
  return __uint_as_float((uint32_t)v << 16);
}
__device__ __forceinline__ void prep_task(const __nv_bfloat16* __restrict__ w, uint4* u, uint32_t id, bool h, int lane) {
  const uint32_t k = id % CH;
  const uint32_t sc = id / CH;
  float g[3][8];
#pragma unroll
  for (int r = 0; r < 3; r++)
#pragma unroll
    for (int e = 0; e < 8; e++) g[r][e] = ldg_bf16(w + (sc * 8 * CH + k) + (r * 3 * CH + e) * CH);
  const Sample smp = sample_w(w, lane);
  const uint32_t s = sc / 24, n = (sc % 24) >> 1, kh = sc & 1;
  const uint32_t jn = (k >> 5) * 4 + ((k >> 1) & 3), row = ((k >> 3) & 3) * 2 + (k & 1);
  u += (((h ? 3 * NSUB : 0) + n) * USLAB + s * UTILE + jn * 256 + kh * 128 + row * 16) >> 4;
  constexpr float nA = -1.f / (2.f * A2 * DD), nB = 1.f / (2.f * B2 * DD);
  constexpr float f0 = nA / S1, f1 = nA / S2, f2 = nB / S3_B, f3 = nB / S4_B;
  const float f4 = n < early(4) ? 1.f / (A2 * B2 * S3_Z0) : 1.f / (A2 * B2), f5 = n < early(5) ? 1.f / S4_I0 : 1.f;
  const float co[3][3] = {{h ? f3 : f0, h ? -PB * f3 : PA * f0, h ? B2 * f3 : A2 * f0},
                          {h ? f4 : f1, h ? 0.f : -PA * f1, h ? 0.f : A2 * f1},
                          {h ? 0.f : f2, h ? 0.f : PB * f2, h ? f5 : B2 * f2}};
  const float sw = __uint_as_float(max(253 - (int)sample_exp(smp), 0) << 23);
#pragma unroll
  for (int r = 0; r < 3; r++)
#pragma unroll
    for (int e = 0; e < 8; e++) g[r][e] *= sw;
#pragma unroll
  for (int p = 0; p < 3; p++) {
    uint32_t o[4];
#pragma unroll
    for (int e = 0; e < 4; e++) {
      float v[2];
#pragma unroll
      for (int q = 0; q < 2; q++) {
        v[q] = co[p][0] * g[0][2 * e + q] + co[p][1] * g[1][2 * e + q] + co[p][2] * g[2][2 * e + q];
        v[q] = __uint_as_float((__float_as_uint(v[q]) + (1u << (12 + 3))) & ~((1u << (13 + 3)) - 1));
      }
      o[e] = pack_f16(v[0], v[1]);
    }
    constexpr uint32_t lim = U_LIM * 0x10001u;
    if (__vimax3_u16x2(__vimax3_u16x2(lim, o[0] & NAN2, o[1] & NAN2), o[2] & NAN2, o[3] & NAN2) != lim) o[0] = NAN2;
    u[p * NSUB * USLAB / 16] = make_uint4(o[0], o[1], o[2], o[3]);
  }
}

constexpr int ROWB = IMG * CH * 2;

__device__ __forceinline__ int region_px(int r) { return (r >> 3) * 8 * IMG + (r & 7) * 64; }

__device__ __noinline__ void direct_patch(const __nv_bfloat16* __restrict__ x, const __nv_bfloat16* __restrict__ w,
                                          __nv_bfloat16* __restrict__ out, int y0, int x0, int lane) {
#pragma unroll 1
  for (int t = 0; t < 8; t++) {
    const int oy = y0 + (t >> 1), ox = x0 + (t & 1) * 8;
    float acc[8][6] = {};
#pragma unroll 1
    for (int rs = 0; rs < 9; rs++) {
      const int iy = oy + rs / 3 - 1, ix = ox + rs % 3 - 1;
      if (iy < 0 || iy >= IMG) continue;
#pragma unroll 1
      for (int c = 0; c < CH; c += 2) {
        uint32_t xv[8], wv[2][3];
#pragma unroll
        for (int p = 0; p < 8; p++)
          xv[p] = (unsigned)(ix + p) < IMG ? *(const uint32_t*)(x + ((size_t)iy * IMG + ix + p) * CH + c) : 0u;
#pragma unroll
        for (int e = 0; e < 2; e++)
#pragma unroll
          for (int m = 0; m < 3; m++) wv[e][m] = *(const uint32_t*)(w + (rs * CH + c + e) * CH + 64 * m + 2 * lane);
#pragma unroll
        for (int p = 0; p < 8; p++)
#pragma unroll
          for (int e = 0; e < 2; e++) {
            const float a = __uint_as_float(e ? xv[p] & 0xFFFF0000u : xv[p] << 16);
#pragma unroll
            for (int m = 0; m < 3; m++) {
              acc[p][2 * m] = fmaf(a, __uint_as_float(wv[e][m] << 16), acc[p][2 * m]);
              acc[p][2 * m + 1] = fmaf(a, __uint_as_float(wv[e][m] & 0xFFFF0000u), acc[p][2 * m + 1]);
            }
          }
      }
    }
#pragma unroll
    for (int p = 0; p < 8; p++)
#pragma unroll
      for (int m = 0; m < 3; m++)
        *(uint32_t*)(out + ((size_t)oy * IMG + ox + p) * CH + 64 * m + 2 * lane) = pack_bf16(acc[p][2 * m], acc[p][2 * m + 1]);
  }
}

struct Descs { uint64_t a[2][6], b[NSTEP / NU]; };
__host__ __device__ constexpr int slot_use(int i) {
  int c = 0;
  for (int j = 0; j < i; j++) c += vslot(step_p(j), step_n(j)) == vslot(step_p(i), step_n(i));
  return c;
}

__host__ __device__ constexpr int out_time(int q) {
  constexpr int t[24] = {55, 56, 57, 58, 59, 60, 61, 62, 63, 64, 65, 66, 67, 68, 69, 70, 72, 73, 74, 75, 76, 77, 78, 79};
  return t[q];
}
__host__ __device__ constexpr int out_at(int t) {
  for (int q = 0; q < 24; q++)
    if (out_time(q) % NSTEP == t) return q;
  return -1;
}
__host__ __device__ constexpr bool out_ok() {
  for (int q = 0; q < 24; q++)
    if (out_time(q) <= last_on(q / 6) || out_time(q) < PIV2 + (q < 12 ? 4 : 6) || out_time(q) >= first_on(q / 6) + NSTEP ||
        (q && out_time(q) <= out_time(q - 1)))
      return false;
  return true;
}
static_assert(out_ok(), "output plan");
constexpr int OUT_END = out_time(23) + 1 - NSTEP;

struct Consumer {
  uint32_t c1[48], c2[48], c3[48], c4[48];
  const uint64_t *descA, *descB;
  uint32_t sb, ebar;
  uint8_t* pout;
  int bid, nblk, nlong;
  uint32_t done;
  uint32_t osc, ymax, redo;
  bool lead, lead2, ok, odd;

  uint32_t one, zero;
  __device__ __forceinline__ bool always() {
    uint32_t v = one;
    asm volatile("" : "+r"(v));
    return v != 0;
  }
  __device__ __forceinline__ void axpy(uint32_t (&a)[48], uint32_t k, uint32_t (&b)[48]) {
    if (always()) {
      reg_fence(a); reg_fence(b);
#pragma unroll
      for (int i = 0; i < 48; i++) {
        a[i] = hfma2(k, b[i], a[i]);
        if (i % 12 == 11) {
          asm volatile("" : "+r"(a[i])::"memory");
          sched_barrier();
        }
      }
      reg_fence(a);
    }
  }
  uint32_t pa[4], pb[4], px[4];
  __device__ __forceinline__ uint32_t to_bf16(uint32_t h) {
    float lo, hi;
    asm("{\n.reg .b16 l, h;\n.reg .b32 m;\nmov.b32 {l, h}, %3;\ncvt.f32.f16 %0, l;\ncvt.f32.f16 %1, h;\n"
        "abs.f16x2 m, %3;\nmax.NaN.f16x2 %2, m, %2;\n}\n" : "=f"(lo), "=f"(hi), "+r"(ymax) : "r"(h));
    return bmul2(pack_bf16(lo, hi), osc);
  }
  template <int Q>
  __device__ __forceinline__ void out_read() {
    const uint32_t(&d)[48] = Q < 6 ? c1 : Q < 12 ? c2 : Q < 18 ? c3 : c4;
    constexpr int o = 16 * (Q % 3) + (Q / 3) % 2;
#pragma unroll
    for (int e = 0; e < 4; e++) {
      pa[e] = to_bf16(d[o + 2 * e]);
      pb[e] = to_bf16(d[o + 8 + 2 * e]);
      px[e] = __shfl_xor_sync(0xffffffffu, odd ? pa[e] : pb[e], 4);
      sched_barrier();
    }
  }
  template <int Q, int EXTRA>
  __device__ __forceinline__ void stg(const uint32_t (&v)[4], uint32_t on) {
    constexpr int y = Q < 6 ? 1 : Q < 12 ? 2 : Q < 18 ? 0 : 3;
    asm volatile("{\n.reg .pred p;\nsetp.ne.u32 p, %5, 0;\n@p st.global" ".cs" ".v4.u32 [%0+%6], {%1,%2,%3,%4};\n}\n" ::"l"(pout), "r"(v[0]),
                 "r"(v[1]), "r"(v[2]), "r"(v[3]), "r"(on), "n"(y * ROWB + (Q / 3) % 2 * 8 * (CH * 2) + Q % 3 * 128 + EXTRA) : "memory");
  }
  template <int Q>
  __device__ __forceinline__ void out_write(uint32_t on) {
    uint32_t u[4], v[4];
#pragma unroll
    for (int e = 0; e < 4; e++) {
      u[e] = odd ? px[e] : pa[e];
      v[e] = odd ? pb[e] : px[e];
    }
    stg<Q, 0>(u, on);
    stg<Q, CH * 2>(v, on);
  }
  __device__ __forceinline__ void range_check() {
    const uint32_t m = __reduce_max_sync(0xffffffffu, max(ymax & 0xFFFFu, ymax >> 16));
    redo |= (uint32_t)(m - Y_MIN >= Y_INF - Y_MIN) << done;
    ymax = 0;
  }
  template <int Q>
  __device__ __forceinline__ void flush() {
    if constexpr (Q < 24) {
      if constexpr (out_time(Q) >= NSTEP) out_read<Q>();
      if constexpr (out_time(Q) >= NSTEP - 1) out_write<Q>(1);
      flush<Q + 1>();
    }
  }
  template <int I>
  __device__ __forceinline__ void hook() {
    constexpr float LP = PB * (PB - PA) / (2.f * A2), LM = PB * (PB + PA) / (2.f * A2);
    constexpr int QW = out_at((I + NSTEP - 1) % NSTEP), QR = out_at(I);
    if constexpr (QW >= 0) { sched_barrier(); out_write<QW>(I > OUT_END ? 1u : done); sched_barrier(); }
    if constexpr (QR >= 0) { sched_barrier(); out_read<QR>(); }
    if constexpr (I == PIV1) axpy(c1, h2const(S3_Z0 * (PB / (2.f * (PB - PA))) / S1), c3);
    if constexpr (I == PIV1 + 1) axpy(c2, h2const(S3_Z0 * (PB / (2.f * (PB + PA))) / S2), c3);
    if constexpr (I == PIV1 + 2) axpy(c4, h2const(S3_Z0 * (A2 * PB) / S4_I0), c3);
    if constexpr (I == PIV1 + 2) axpy(c3, h2const(S4_I0 * (1.f / (2.f * PB * DD)) / S3_B), c4);
    if constexpr (I == PIV1 + 3) axpy(c1, h2const(S4_I0 * (-1.f / (2.f * PA * DD)) / S1), c4);
    if constexpr (I == PIV1 + 4) axpy(c2, h2const(S4_I0 * (1.f / (2.f * PA * DD)) / S2), c4);
    if constexpr (I == 20) {
      static_assert(OUT_END < 20, "pointer update");
      range_check();
      osc = lds32(sb + OFF_OSC);
      const int r = bid + done * nblk, d = region_px(r & 0xffff) - (done ? region_px((r - nblk) & 0xffff) : region_px(r - nblk));
      asm volatile("mad.wide.s32 %0, %1, 384, %0;" : "+l"(pout) : "r"(d));
    }
    if constexpr (I == 30) { if (bid >= nlong && done == 1) spin_cycles(40000); }
    if constexpr (I == PIV2) axpy(c1, h2const(S3_B * (B2 / A2) / S1), c3);
    if constexpr (I == PIV2) axpy(c2, h2const(S3_B * (B2 / A2) / S2), c3);
    if constexpr (I == PIV2 + 1) axpy(c4, h2const(-S3_B / S4_B), c3);
    if constexpr (I == PIV2 + 1) axpy(c1, h2const(S4_B * LP / S1), c4);
    if constexpr (I == PIV2 + 2) axpy(c2, h2const(S4_B * LM / S2), c4);
    if constexpr (I == PIV2 + 2) axpy(c3, h2const(S4_B * (-DD / A2)), c4);
    if constexpr (I == PIV2 + 3) { axpy(c1, h2const(-1.f / (2.f * PA)), c2); axpy(c2, h2const(PA), c1); }
    if constexpr (I == PIV2 + 4) axpy(c4, h2const(A2), c1);
    if constexpr (I == PIV2 + 5) axpy(c3, h2const(1.f / A2), c2);
  }

  template <int I>
  __device__ __forceinline__ void steps() {
    if constexpr (I < NSTEP) {
      uint32_t(&d)[48] = step_acc(I) == 0 ? c1 : step_acc(I) == 1 ? c2 : step_acc(I) == 2 ? c3 : c4;
      constexpr int vo = vslot(step_p(I), step_n(I)) * VSLOT, uo = (I % NU) * USLAB;
      constexpr int J = (I + 1) % NSTEP;
      if (!ok) {
        mbar_wait_short(sb + BAR_UFULL + 8 * (I % NU), (I / NU) & 1);
        if constexpr (first_use(step_n(I)) == I) mbar_wait_short(sb + BAR_VFULL + 8 * (step_n(I) % NB), step_n(I) / NB);
      }
      const uint64_t da = descA[slot_use(I)], db = descB[I / NU];
      wg_fence();
      wgmma192<vo, uo>(d, da, db, first_on(step_acc(I)) == I ? 0u : 1u);
      wgmma192<vo + 16, uo + UTILE>(d, da, db, 1u);
      wgmma192<vo + 32, uo + 2 * UTILE>(d, da, db, 1u);
      wg_commit();
      ok = mbar_test(sb + BAR_UFULL + 8 * (J % NU), ((J / NU) & 1) ^ zero);
      if constexpr (first_use(step_n(J)) == J) ok &= mbar_test(sb + BAR_VFULL + 8 * (step_n(J) % NB), (step_n(J) / NB) ^ zero);
      hook<I>();
      wg_wait<0>();
      reg_fence(d);
      if (lead) mbar_arrive(sb + BAR_UEMPTY + 8 * (I % NU));
      if constexpr (gate_of(I) >= 0) { if (lead) mbar_arrive(sb + BAR_GATE + 8 * (gate_of(I) % NB)); }
      steps<I + 1>();
    }
  }
};

struct SlotTab { uint32_t off[NSUB][8]; };
constexpr SlotTab make_slots() {
  SlotTab t = {};
  for (int n = 0; n < NSUB; n++)
    for (int p = 0; p < 6; p++) t.off[n][p] = vslot(p, n) * VSLOT;
  return t;
}
__constant__ SlotTab c_slots = make_slots();

constexpr int PF_X = 3, PF_Y = 10;
constexpr int PF_NG = CH / 64, PF_NB = 66 / PF_X * (10 / PF_Y);
__host__ __device__ constexpr uint32_t pf_box(int g, int q) {
  return 1u << 31 | (g / PF_NG) << 24 | (g % PF_NG * 64) << 16 | (q / (10 / PF_Y) * PF_X) << 8 | q % (10 / PF_Y) * PF_Y;
}
struct PfTab { uint32_t e[NSTEP][2], first[NSTEP], slab[2 * NSTEP]; int nfirst; };
constexpr PfTab make_pf() {
  PfTab t = {};
  for (int i = 0; i < 2 * NSTEP; i++) t.slab[i] = (step_p(i % NSTEP) * NSUB + step_n(i % NSTEP)) * USLAB;
  constexpr int win[6] = {23, 39, 40, 78, 79, 95};
  for (int g = 0; g < PF_NG; g++)
    for (int q = 0; q < PF_NB; q++) {
      const int i = win[2 * g] + q * (win[2 * g + 1] - win[2 * g]) / PF_NB;
      t.e[i % NSTEP][t.e[i % NSTEP][0] != 0] = pf_box(i < NSTEP ? g + PF_NG : g, q);
      if (i < NSTEP && g > 0) t.first[t.nfirst++] = pf_box(g, q);
    }
  return t;
}
constexpr int NFIRST = make_pf().nfirst;
__constant__ PfTab c_pf = make_pf();
template <bool LOAD>
__device__ __forceinline__ void touch(const void* p, int lane) {
  if (LOAD) asm volatile("cp.async.ca.shared.global.L2::128B [%0], [%1], 4;" ::"r"(SMEM_BASE + OFF_DUMMY + lane * 4), "l"(p) : "memory");
  else asm volatile("prefetch.global.L2 [%0];" ::"l"(p) : "memory");
}
__device__ __forceinline__ void prefetch_x(const __nv_bfloat16* x, uint32_t e, int r, int bid, int nblk, int nlong, int lane) {
  const int rr = r + ((e >> 24) & 1) * nblk;
  const int px = (rr & 7) * 64 - 1 + ((e >> 8) & 255) + lane / 10, py = (rr >> 3) * 8 - 1 + lane % 10;
  const int owner = (py >> 3) * 8 + (px >> 6) - rr + bid;
  const bool alongside = owner != bid && (unsigned)owner < (unsigned)nblk && (!40000 || (owner < nlong) == (bid < nlong));
  if ((int)e < 0 && lane < 30 && (unsigned)px < IMG && (unsigned)py < IMG && (7 == 1 || 7 == 5 || !alongside))
    touch<(7 == 5 || 7 == 6)>(x + ((py & 0xffff) * IMG + px) * CH + ((e >> 16) & 255), lane);
}

__global__ void __launch_bounds__(384, 1) __cluster_dims__(0 ? 2 : 1, 1, 1)
conv_kernel(const __grid_constant__ CUtensorMap tmX, const __grid_constant__ CUtensorMap tmP, const __nv_bfloat16* __restrict__ xin, const __nv_bfloat16* __restrict__ wgt,
            __nv_bfloat16* __restrict__ out, uint4* ubuf, uint32_t* arrived, int nblk, int nlong, int nmax, const __grid_constant__ Descs desc) {
  extern __shared__ uint8_t smem_raw[];
  const int tid = threadIdx.x, lane = tid & 31, bid = blockIdx.x;
  if (tid < 256) {
    cluster_arrive_relaxed();
#pragma unroll 1
    for (uint32_t id = bid * 128 + (tid & 127); id < NPREP; id += nblk * 128) prep_task(wgt, ubuf, id, tid >= 128, lane);
    asm volatile("bar.arrive 1, 288;" ::: "memory");
  }
  const uint32_t sb = smem_u32(smem_raw);
  if ((sb & 0xFFFFFFu) != SMEM_BASE) __trap();
  const int warp = __shfl_sync(0xffffffffu, tid >> 5, 0);

  if (warp < 8) {
    const int wg = warp >> 2;
    cluster_wait();
    asm volatile("setmaxnreg.inc.sync.aligned.u32 224;");
    Consumer c;
    c.sb = sb;
#pragma unroll
    for (int i = 0; i < 48; i++) { c.c1[i] = 0; c.c2[i] = 0; c.c3[i] = 0; c.c4[i] = 0; }
#pragma unroll
    for (int e = 0; e < 4; e++) c.pa[e] = c.pb[e] = c.px[e] = 0;
    c.descA = desc.a[wg];
    c.descB = desc.b;
    c.lead = (tid & 127) == 0;
    c.lead2 = (tid & 127) < 2;
    c.ebar = (sb + BAR_UEMPTY) ^ ((lane & 1) << 24);
    c.one = __shfl_sync(0xffffffffu, nblk, 0);
    c.zero = __shfl_sync(0xffffffffu, nblk >> 20, 0);
    c.ok = false;
    c.bid = bid;
    c.nblk = nblk;
    c.nlong = nlong;
    c.odd = (lane >> 2) & 1;
    c.pout = (uint8_t*)out + (long long)(region_px(bid - nblk) + wg * 4 * IMG + (warp & 3) * 16 + (lane >> 3) * 2) * (CH * 2) + (lane & 7) * 16;
    c.done = c.osc = c.ymax = c.redo = 0;
#pragma unroll 1
    do {
      wg_wait<0>();
      c.steps<0>();
      c.done++;
    } while (bid + (int)c.done * nblk < NREG);
    c.flush<0>();
    c.range_check();
    cluster_arrive_relaxed();
    if (c.redo >> 1) {
      __syncwarp();
      for (int i = 0; i < (int)c.done; i++)
        if ((c.redo >> (i + 1)) & 1) {
          const int r = bid + i * nblk;
          direct_patch(xin, wgt, out, (r >> 3) * 8 + wg * 4, (r & 7) * 64 + (warp & 3) * 16, lane);
        }
    }
    cluster_wait();
  } else {
    asm volatile("setmaxnreg.dec.sync.aligned.u32 56;");
    if (tid == 352) {
      for (int i = 0; i < NU; i++) { mbar_init(sb + BAR_UFULL + 8 * i, 1); mbar_init(sb + BAR_UEMPTY + 8 * i, 0 ? 4 : 2); }
      for (int i = 0; i < NB; i++) { mbar_init(sb + BAR_VFULL + 8 * i, 3); mbar_init(sb + BAR_GATE + 8 * i, 2); }
      mbar_init(sb + BAR_DUMMY, 1);
      asm volatile("fence.mbarrier_init.release.cluster;" ::: "memory");
      fence_async();
    }
    __syncwarp();
    cluster_arrive_relaxed();
    const int nitem = nmax - (bid >= nlong);
    if (warp == 11) {
      const uint32_t half = 0 ? (bid & 1) * (USLAB / 2) : 0;
      const uint8_t* ubase = (const uint8_t*)ubuf + half;
      const uint32_t slab0 = c_pf.slab[NU + (nblk >> 20)];
      uint32_t epoch;
      asm volatile("ld.relaxed.gpu.global.u32 %0, [%1];" : "=r"(epoch) : "l"(arrived) : "memory");
      cluster_wait();
      asm volatile("bar.sync 1, 288;" ::: "memory");
      sched_barrier();
      grid_barrier(arrived, nblk, epoch);
      asm volatile("fence.proxy.async.global;" ::: "memory");
#pragma unroll
      for (int s = 0; s < NU; s++) load_u_warp(sb + OFF_U + half + s * USLAB, ubase + (step_p(s) * NSUB + step_n(s)) * USLAB, sb + BAR_UFULL + 8 * s);
      const uint8_t* src = ubase + slab0;
      uint32_t dst = sb + OFF_U + half, ebar = sb + BAR_UEMPTY, upar = 0;
      int i = 0, r = bid, extra = 0;
      const int ulane = (bid * (0 ? 0 : 2) + lane) % 144 * 128;
      auto prefetch = [&](uint32_t e) {
        const int rr = r + ((e >> 24) & 1) * nblk;
        if ((int)e < 0 && rr < NREG)
          asm volatile("{\n.reg .pred p;\nelect.sync _|p, 0xffffffff;\n"
                       "@p mbarrier.expect_tx.shared::cta.b64 [%2], %6;\n"
                       "@p cp.async.bulk.tensor.3d.shared::cluster.global.mbarrier::complete_tx::bytes [%0], [%1, {%3, %4, %5}], [%2];\n}\n" ::"r"(sb + OFF_DUMMY),
                       "l"(&tmP), "r"(sb + BAR_DUMMY), "r"((e >> 16) & 255), "r"((rr & 7) * 64 - 1 + ((e >> 8) & 255)), "r"(((rr & 0xffff) >> 3) * 8 - 1 + (e & 255)),
                       "n"(PF_X * PF_Y * 16) : "memory");
      };
#pragma unroll 1
      for (; extra < 5; extra++) prefetch(c_pf.first[extra]);
#pragma unroll 1
      for (int left = nitem * NSTEP - NU; left > 0; left--) {
        mbar_wait(ebar, upar);
        load_u_warp(dst, src, ebar - (BAR_UEMPTY - BAR_UFULL));
        {
          const uint8_t* pu = (const uint8_t*)ubuf + c_pf.slab[i + 9];
          if (0 ? lane < 0 : bid < 72 && lane < 2) touch<(0 > 0)>(pu + ulane, lane);
        }
        for (int k = 0; k < 1; k++) if (extra < NFIRST && i >= 0) prefetch(c_pf.first[extra++]);
        prefetch(c_pf.e[i][0]);
        if (c_pf.e[i][1]) prefetch(c_pf.e[i][1]);
        if (i == NSTEP - 1) r += nblk;
        i = i == NSTEP - 1 ? 0 : i + 1;
        src = ubase + c_pf.slab[i + NU];
        const int s = i & (NU - 1);
        dst = sb + OFF_U + half + s * USLAB;
        ebar = sb + BAR_UEMPTY + 8 * s;
        if (s == 0) upar ^= 1;
      }
#pragma unroll 1
      for (int s = 0; s < NU; s++) mbar_wait(sb + BAR_UEMPTY + 8 * s, 1);
      if (lane == 0) mbar_arrive(sb + BAR_DUMMY);
      mbar_wait(sb + BAR_DUMMY, 0);
    } else {
      const int w = warp - 8, col = (lane >> 1) & 7, chunk = lane >> 4;
      const uint32_t xbox = sb + OFF_X + w * 3 * XBOX, xbar = sb + BAR_XFULL + 24 * w;
      const uint32_t xl = xbox + col * 32 + ((chunk ^ (col >> 2)) << 4) + (lane & 1) * 8;
      const uint32_t vl = sb + OFF_V + chunk * VROW + w * 128 + (lane & 15) * 8;
      const bool in_row = w < 2 || col < 2;
      if (lane < 3) mbar_init(xbar + 8 * lane, 1);
      fence_async();
      asm volatile("prefetch.tensormap [%0];" ::"l"(&tmX) : "memory");
      const Sample ws = sample_w(wgt, lane), xs = sample_x(xin, bid, lane);
      asm volatile("bar.sync 2, 128;" ::: "memory");
      sched_barrier();
#pragma unroll
      for (int j = 0; j < 3; j++) tma_box_warp(xbox + j * XBOX, &tmX, xbar + 8 * j, XBOX, 0, (bid & 7) * 64 - 1 + w * 8 + j * 24, ((bid & 0xffff) >> 3) * 8 - 1);
      sched_barrier();
      uint32_t xsc;
      {
        const int ex = sample_exp(xs), eo = ex + (int)sample_exp(ws) - (111 + X_EXP), es = 127 + X_EXP - ex;
        xsc = es >= 1 && eo >= 1 && eo <= 254 ? es * 0x00800080u : NAN2;
        asm volatile("st.shared.u32 [%0], %1;" ::"r"(sb + OFF_OSC), "r"(eo * 0x00800080u) : "memory");
      }
      constexpr uint32_t gate_par = [] { uint32_t m = 0; for (int n = 0; n < NSUB; n++) if ((n / NB) ^ (gate(n % NB) < 0)) m |= 1u << n; return m; }();
      constexpr uint32_t LIM2 = X_LIM * 0x10001u;
      cluster_wait();
      mbar_wait(xbar, 0);
      uint2 d[10];
#pragma unroll
      for (int i = 0; i < 6; i++) d[i] = lds64(xl + i * 256);
      auto conv = [&](uint2& v, uint32_t m) {
        const uint32_t tx = bmul2(v.x, xsc), ty = bmul2(v.y, xsc), ux = tx & NAN2, uy = ty & NAN2;
        v = make_uint2(ux * 7 + tx, uy * 7 + ty);
        return __vimax3_u16x2(m, ux, uy);
      };
      uint32_t so[6] = {};
      auto planes = [&](const uint2* h, uint32_t m, uint32_t a, bool on) {
        constexpr uint32_t NB2 = h2const(-B2), NA2 = h2const(-A2);
        const uint2 e1 = fma4(NB2, h[2], h[4]), e2 = fma4(NA2, h[2], h[4]);
        sts64(a + so[4], fma4(NA2, fma4(NB2, h[0], h[2]), e1), on);
        const uint2 o1 = fma4(NB2, h[1], h[3]), o2 = fma4(NA2, h[1], h[3]);
        sts64(a + so[5], fma4(NA2, o1, fma4(NB2, h[3], h[5])), on);
        uint2 v = fma4(h2const(PA), o1, e1);
        if (m != LIM2) v.x = NAN2;
        sts64(a + so[0], v, on);
        sts64(a + so[1], fma4(h2const(-PA), o1, e1), on);
        sts64(a + so[2], fma4(h2const(PB), o2, e2), on);
        sts64(a + so[3], fma4(h2const(-PB), o2, e2), on);
      };
      int r = bid, n = 0;
      uint32_t par = 0;
#pragma unroll 1
      for (int left = nitem * NSUB; left > 0; left--) {
        const int nb = n >= NB ? n - NB : n;
#pragma unroll
        for (int p = 0; p < 6; p++) so[p] = c_slots.off[n][p];
        const uint32_t gpar = (gate_par >> n) & 1;
        if (++n == NSUB) { n = 0; r += nblk; }
        const int fc = n * 16, fx = (r & 7) * 64 - 1 + w * 8, fy = ((r & 0xffff) >> 3) * 8 - 1;
        const uint64_t pol = (n & (64 / 16 - 1)) == 64 / 16 - 1 ? 0x12F0000000000000ull : 0x1000000000000000ull;
#pragma unroll
        for (int j = 0; j < 3; j++) {
          const uint32_t nbar = xbar + 8 * ((j + 1) % 3), npar = j == 2 ? par ^ 1 : par;
          const bool on = j < 2 || in_row;
#pragma unroll
          for (int i = 6; i < 10; i++) d[i] = lds64(xl + j * XBOX + i * 256);
          const bool xok = mbar_test(nbar, npar);
          sched_barrier();
          const uint32_t m45 = conv(d[5], conv(d[4], LIM2));
          const uint32_t ma = conv(d[3], conv(d[1], conv(d[0], conv(d[2], m45))));
          if (j == 0) { mbar_wait(sb + BAR_GATE + 8 * nb, gpar); }
          planes(d, ma, vl + j * 384, on);
          sched_barrier();
          const uint32_t mb = conv(d[9], conv(d[7], conv(d[6], conv(d[8], m45))));
          tma_box_warp(xbox + j * XBOX, &tmX, xbar + 8 * j, XBOX | (mb & 0x8000u), fc, fx + j * 24, fy, pol);
          uint2 h[6];
#pragma unroll
          for (int i = 0; i < 6; i++) h[i] = d[4 + i];
          mbar_wait(nbar, npar, xok);
#pragma unroll
          for (int i = 0; i < 6; i++) d[i] = lds64(xl + ((j + 1) % 3) * XBOX + i * 256);
          sched_barrier();
          planes(h, mb, vl + j * 384 + VPIECE, on);
          sched_barrier();
        }
        fence_async();
        asm volatile("{\n.reg .pred p;\nelect.sync _|p, 0xffffffff;\n@p mbarrier.arrive.shared::cta.b64 _, [%0];\n}\n" ::"r"(sb + BAR_VFULL + 8 * nb) : "memory");
        par ^= 1;
      }
      mbar_wait(xbar + 8, par);
      mbar_wait(xbar + 16, par);
    }
    asm volatile("cp.async.wait_all;" ::: "memory");
    cluster_arrive_relaxed();
  }
}

constexpr uint64_t make_desc(uint32_t off, uint32_t lbo, uint32_t sbo) {
  return (uint64_t)((SMEM_BASE + off) >> 4) | ((uint64_t)(lbo >> 4) << 16) | ((uint64_t)(sbo >> 4) << 32);
}

typedef CUresult (*EncodeFn)(CUtensorMap*, CUtensorMapDataType, cuuint32_t, void*, const cuuint64_t*, const cuuint64_t*,
                             const cuuint32_t*, const cuuint32_t*, CUtensorMapInterleave, CUtensorMapSwizzle,
                             CUtensorMapL2promotion, CUtensorMapFloatOOBfill);

}

extern "C" void kernel_launch(void* const* d_in, const int* in_sizes, int n_in, void* d_out, int out_size) {
  static EncodeFn enc = nullptr;
  static int nblk = 0;
  static uint4* ubuf;
  static uint32_t* arrived;
  if (!enc) {
    cudaGetSymbolAddress((void**)&ubuf, g_U);
    cudaGetSymbolAddress((void**)&arrived, g_arrived);
    cudaDriverEntryPointQueryResult qr;
    cudaGetDriverEntryPoint("cuTensorMapEncodeTiled", (void**)&enc, cudaEnableDefault, &qr);
    cudaFuncSetAttribute(conv_kernel, cudaFuncAttributeMaxDynamicSharedMemorySize, SMEM_BYTES);
    int dev;
    cudaGetDevice(&dev);
    cudaDeviceGetAttribute(&nblk, cudaDevAttrMultiProcessorCount, dev);
  }
  CUtensorMap tmX, tmP;
  const cuuint64_t dims[3] = {CH, IMG, IMG};
  const cuuint64_t strides[2] = {CH * 2, (cuuint64_t)CH * 2 * IMG};
  const cuuint32_t es[3] = {1, 1, 1};
  const cuuint32_t boxX[3] = {16, 8, 10}, boxP[3] = {8, PF_X, PF_Y};
  enc(&tmP, CU_TENSOR_MAP_DATA_TYPE_BFLOAT16, 3, d_in[0], dims, strides, boxP, es, CU_TENSOR_MAP_INTERLEAVE_NONE,
      CU_TENSOR_MAP_SWIZZLE_NONE, CU_TENSOR_MAP_L2_PROMOTION_L2_128B, CU_TENSOR_MAP_FLOAT_OOB_FILL_NONE);
  enc(&tmX, CU_TENSOR_MAP_DATA_TYPE_BFLOAT16, 3, d_in[0], dims, strides, boxX, es, CU_TENSOR_MAP_INTERLEAVE_NONE,
      CU_TENSOR_MAP_SWIZZLE_32B, CU_TENSOR_MAP_L2_PROMOTION_L2_64B, CU_TENSOR_MAP_FLOAT_OOB_FILL_NONE);
  Descs desc;
  for (int i = 0; i < 6; i++) { desc.a[0][i] = make_desc(OFF_V, VROW, 128); desc.a[1][i] = make_desc(OFF_V + VPIECE, VROW, 128); }
  for (int i = 0; i < NSTEP / NU; i++) desc.b[i] = make_desc(OFF_U, 128, 256);
  conv_kernel<<<nblk, 384, SMEM_BYTES>>>(tmX, tmP, (const __nv_bfloat16*)d_in[0], (const __nv_bfloat16*)d_in[1], (__nv_bfloat16*)d_out, ubuf, arrived, nblk,
                                         NREG % nblk ? NREG % nblk : nblk, (NREG + nblk - 1) / nblk, desc);
}
```

```cpp
#include <cuda_runtime.h>
#include <cuda_bf16.h>
#include <cuda.h>
#include <stdint.h>

namespace {

constexpr int IMG = 512, CH = 192;
constexpr float PA = 0.6875f, PB = 1.5f;
constexpr float A2 = PA * PA, B2 = PB * PB, DD = B2 - A2;

constexpr int NSTEP = 72, NSUB = 12;
__host__ __device__ constexpr int sched(int i) {
  constexpr int t[NSTEP] = {0x00, 0x10, 0x20, 0x01, 0x11, 0x21, 0x02, 0x12, 0x22, 0x30, 0x31, 0x32, 0x23, 0x33, 0x03, 0x13, 0x24, 0x34, 0x04, 0x14, 0x25, 0x35, 0x05, 0x15, 0x26, 0x36, 0x06, 0x16, 0x27, 0x37, 0x07, 0x17, 0x28, 0x38, 0x08, 0x18, 0x29, 0x39, 0x09, 0x19, 0x2a, 0x3a, 0x0a, 0x1a, 0x2b, 0x3b, 0x1b, 0x0b, 0x40, 0x41, 0x50, 0x42, 0x51, 0x43, 0x44, 0x52, 0x45, 0x46, 0x53, 0x47, 0x48, 0x49, 0x4a, 0x4b, 0x54, 0x55, 0x56, 0x57, 0x58, 0x59, 0x5a, 0x5b};
  return t[i];
}
constexpr int PIV1 = 0, PIV2 = 45;
__host__ __device__ constexpr int step_p(int i) { return sched(i) >> 4; }
__host__ __device__ constexpr int step_n(int i) { return sched(i) & 15; }
__host__ __device__ constexpr int step_acc(int i) { return step_p(i) < 4 ? step_p(i) : step_p(i) - 2; }
__host__ __device__ constexpr int first_on(int acc) {
  for (int i = 0; i < NSTEP; i++)
    if (step_acc(i) == acc) return i;
  return -1;
}
__host__ __device__ constexpr int last_on(int acc) {
  for (int i = NSTEP - 1; i >= 0; i--)
    if (step_acc(i) == acc) return i;
  return -1;
}
__host__ __device__ constexpr int find_step(int p, int n) {
  for (int i = 0; i < NSTEP; i++)
    if (sched(i) == p * 16 + n) return i;
  return -1;
}
__host__ __device__ constexpr int first_use(int n) {
  for (int i = 0; i < NSTEP; i++)
    if (step_n(i) == n) return i;
  return -1;
}
constexpr float S1 = 1.f / PA, S2 = 1.f / (2.f * A2);
constexpr float S3_Z0 = 0 == 2 ? 0.5f : 1.f, S3_B = -A2 / (2.f * DD);
constexpr float S4_I0 = 2.f, S4_B = S4_I0 * (-1.f / (2.f * PB * DD));

constexpr int NV = 32, NB = 6;
__host__ __device__ constexpr int vslot(int p, int n) {
  constexpr int t[6][NSUB] = {{23, 22, 10, 9, 12, 23, 30, 14, 24, 27, 28, 27}, {30, 4, 14, 28, 24, 27, 19, 25, 23, 30, 23, 26}, {24, 6, 27, 15, 16, 10, 26, 15, 17, 22, 25, 30}, {25, 26, 8, 13, 17, 22, 28, 22, 26, 19, 24, 22}, {20, 29, 21, 2, 4, 6, 8, 10, 12, 14, 16, 18}, {31, 0, 1, 3, 5, 7, 9, 11, 13, 15, 17, 19}};
  return t[p][n];
}
__host__ __device__ constexpr int gate(int n) {
  constexpr int t[NSUB] = {-21, -15, -9, -2, 5, 11, 16, 21, 26, 30, 35, 39};
  return t[n];
}
__host__ __device__ constexpr int gate_of(int i) {
  for (int n = 0; n < NSUB; n++)
    if ((gate(n) + NSTEP) % NSTEP == i) return n;
  return -1;
}
__host__ __device__ constexpr bool gates_ok() {
  for (int n = 0; n < NSUB; n++) {
    for (int p = 0; p < 6; p++)
      for (int d = 1; d <= NSUB; d++)
        for (int q = 0; q < 6; q++) {
          const int m = (n - d + NSUB) % NSUB;
          if (vslot(q, m) == vslot(p, n) && (find_step(q, m) - (n - d < 0 ? NSTEP : 0) > gate(n) || (m == n && p != q))) return false;
        }
    if (n > 0 && (gate(n) <= gate(n - 1) || first_use(n) <= first_use(n - 1))) return false;
    if (gate(n) >= first_use(n)) return false;
    if (gate((n + NB) % NSUB) + (n >= NB ? NSTEP : 0) < first_use(n)) return false;
  }
  return gate(0) + NSTEP > gate(NSUB - 1) && gate(NB) >= 0;
}
static_assert(gates_ok(), "gates");

constexpr int UTILE = CH * 16 * 2;
constexpr int USLAB = 3 * UTILE;
constexpr int NU = 4;
constexpr int VROW = 66 * 16;
constexpr int VPIECE = 2 * VROW;
constexpr int VSLOT = 2 * VPIECE;
constexpr int XBOX = 10 * 8 * 32;
constexpr int XHBOX = 10 * 2 * 32;
static_assert(NSTEP % (2 * NU) == 0, "static ring parity");

constexpr int OFF_X = 0;
constexpr int OFF_DUMMY = OFF_X + 8 * XBOX + XHBOX;
constexpr int OFF_U = OFF_DUMMY + 768;
constexpr int OFF_V = OFF_U + NU * USLAB;
constexpr int OFF_BAR = OFF_V + NV * VSLOT;
constexpr int BAR_UFULL = OFF_BAR;
constexpr int BAR_UEMPTY = BAR_UFULL + 8 * NU;
constexpr int BAR_XFULL = BAR_UEMPTY + 8 * NU;
constexpr int BAR_VFULL = BAR_XFULL + 8 * 9;
constexpr int BAR_GATE = BAR_VFULL + 8 * NB;
constexpr int BAR_DUMMY = BAR_GATE + 8 * NB;
constexpr int OFF_OSC = BAR_DUMMY + 8;
constexpr int NBAR = (OFF_OSC - OFF_BAR) / 8;
constexpr int SMEM_BYTES = OFF_OSC + 8;
constexpr uint32_t SMEM_BASE = 1024;
static_assert(SMEM_BYTES <= 232448, "smem");

constexpr int NREG = 512;

__device__ __align__(128) uint4 g_U[NSTEP * USLAB / 16];
__device__ uint32_t g_arrived[3 * 32];

__device__ __forceinline__ uint32_t smem_u32(const void* p) { return (uint32_t)__cvta_generic_to_shared(p); }
__device__ __forceinline__ void mbar_init(uint32_t a, int c) {
  asm volatile("mbarrier.init.shared::cta.b64 [%0], %1;" ::"r"(a), "r"(c) : "memory");
}
__device__ __forceinline__ void mbar_arrive(uint32_t a) {
  asm volatile("mbarrier.arrive.shared::cta.b64 _, [%0];" ::"r"(a) : "memory");
}
__device__ __forceinline__ void mbar_wait(uint32_t a, uint32_t parity, uint32_t skip = 0) {
  asm volatile(
      "{\n"
      ".reg .pred p;\n"
      ".reg .u32 n;\n"
      "setp.ne.u32 p, %2, 0;\n"
      "@p bra.uni LAB_DONE;\n"
      "mov.u32 n, 0;\n"
      "LAB_WAIT:\n"
      "mbarrier.try_wait.parity.shared::cta.b64 p, [%0], %1;\n"
      "@p bra.uni LAB_DONE;\n"
      "add.u32 n, n, 1;\n"
      "setp.lt.u32 p, n, 4000000;\n"
      "@p bra.uni LAB_WAIT;\n"
      "trap;\n"
      "LAB_DONE:\n"
      "}\n" ::"r"(a), "r"(parity), "r"(skip) : "memory");
}
__device__ __forceinline__ void mbar_wait_short(uint32_t a, uint32_t parity) {
  asm volatile("{\n.reg .pred p;\nLAB_WAIT:\nmbarrier.try_wait.parity.shared::cta.b64 p, [%0], %1;\n@!p bra.uni LAB_WAIT;\n}\n" ::"r"(a),
               "r"(parity) : "memory");
}
__device__ __forceinline__ bool mbar_test(uint32_t a, uint32_t parity) {
  uint32_t ok;
  asm volatile("{\n.reg .pred p;\nmbarrier.test_wait.parity.shared::cta.b64 p, [%1], %2;\nselp.u32 %0, 1, 0, p;\n}\n"
               : "=r"(ok) : "r"(a), "r"(parity) : "memory");
  return ok;
}
__device__ __forceinline__ void fence_async() { asm volatile("fence.proxy.async.shared::cta;" ::: "memory"); }
__device__ __forceinline__ void tma_box_warp(uint32_t dst, const CUtensorMap* tm, uint32_t bar, uint32_t bytes, int c, int x, int y) {
  asm volatile(
      "{\n.reg .pred p;\nelect.sync _|p, 0xffffffff;\n"
      "@p mbarrier.arrive.expect_tx.shared::cta.b64 _, [%2], %6;\n"
      "@p cp.async.bulk.tensor.3d.shared::cluster.global.mbarrier::complete_tx::bytes [%0], [%1, {%3, %4, %5}], [%2];\n}\n" ::"r"(dst),
      "l"(tm), "r"(bar), "r"(c), "r"(x), "r"(y), "r"(bytes) : "memory");
}
__device__ __forceinline__ void load_u_warp(uint32_t dst, const void* src, uint32_t bar) {
  asm volatile("{\n.reg .pred p;\nelect.sync _|p, 0xffffffff;\n"
               "@p mbarrier.arrive.expect_tx.shared::cta.b64 _, [%2], %3;\n"
               "@p cp.async.bulk.shared::cluster.global.mbarrier::complete_tx::bytes [%0], [%1], %3, [%2];\n}\n" ::"r"(dst),
               "l"(src), "r"(bar), "n"(USLAB) : "memory");
}
__device__ __forceinline__ uint2 lds64(uint32_t a) {
  uint2 v;
  asm volatile("ld.shared.v2.u32 {%0,%1}, [%2];" : "=r"(v.x), "=r"(v.y) : "r"(a) : "memory");
  return v;
}
__device__ __forceinline__ uint32_t lds32(uint32_t a) {
  uint32_t v;
  asm volatile("ld.shared.u32 %0, [%1];" : "=r"(v) : "r"(a) : "memory");
  return v;
}
__device__ __forceinline__ void sts64(uint32_t a, uint2 v, bool on) {
  v.x &= 0xFFFCFFFCu; v.y &= 0xFFFCFFFCu;
  if (on) asm volatile("st.shared.v2.u32 [%0], {%1,%2};" ::"r"(a), "r"(v.x), "r"(v.y) : "memory");
}
__device__ __forceinline__ void sched_barrier() { asm volatile("pmevent 0;" ::: "memory"); }
__device__ __forceinline__ void spin_cycles(uint32_t n) {
  asm volatile(
      "{\n.reg .pred p;\n.reg .u32 t0, t;\n"
      "mov.u32 t0, %%clock;\n"
      "LAB_SPIN:\n"
      "nanosleep.u32 50;\n"
      "mov.u32 t, %%clock;\nsub.u32 t, t, t0;\nsetp.lt.u32 p, t, %0;\n"
      "@p bra.uni LAB_SPIN;\n}\n" ::"r"(n) : "memory");
}
__device__ __forceinline__ void spin_until(uint32_t t0, uint32_t n) {
  asm volatile("{\n.reg .pred p;\n.reg .u32 t;\nLAB_SPIN:\nmov.u32 t, %%clock;\nsub.u32 t, t, %0;\nsetp.lt.u32 p, t, %1;\n@p bra.uni LAB_SPIN;\n}\n" ::"r"(t0),
               "r"(n) : "memory");
}
__device__ __forceinline__ uint32_t now() {
  uint32_t t;
  asm volatile("mov.u32 %0, %%clock;" : "=r"(t)::"memory");
  return t;
}
__device__ __forceinline__ uint32_t stage_enter(uint32_t* ctr, int lane) {
  uint32_t old;
  asm volatile("{\n.reg .pred p;\nsetp.eq.u32 p, %2, 0;\nld.relaxed.gpu.global.u32 %0, [%1];\n@p red.relaxed.gpu.global.add.u32 [%1], %3;\n}"
               : "=r"(old) : "l"(ctr), "r"(lane), "r"(lane + 1) : "memory");
  return old;
}
__device__ __forceinline__ void stage_wait(const uint32_t* ctr, uint32_t old) {
  asm volatile(
      "{\n.reg .pred p;\n.reg .u32 v, i;\n"
      "mov.u32 i, 0;\n"
      "LAB_POLL:\n"
      "ld.acquire.gpu.global.u32 v, [%0];\n"
      "xor.b32 v, v, %1;\nsetp.lt.s32 p, v, 0;\n"
      "@p bra.uni LAB_OUT;\n"
      "add.u32 i, i, 1;\nsetp.lt.u32 p, i, 4000000;\n"
      "@p bra.uni LAB_POLL;\n"
      "trap;\n"
      "LAB_OUT:\n"
      "fence.proxy.async.global;\n}\n" ::"l"(ctr), "r"(old) : "memory");
}
__device__ __forceinline__ void cluster_arrive_relaxed() { asm volatile("barrier.cluster.arrive.relaxed.aligned;" ::: "memory"); }
__device__ __forceinline__ void cluster_wait() { asm volatile("barrier.cluster.wait.acquire.aligned;" ::: "memory"); }

__host__ __device__ constexpr uint32_t h2const(float v) {
  double a = v < 0 ? -v : v;
  int e = 15;
  while (a >= 2) { a /= 2; e++; }
  while (a < 1) { a *= 2; e--; }
  const uint32_t h = (v < 0 ? 0x8000u : 0u) | ((e << 10) + (uint32_t)((a - 1) * 1024 + 0.5));
  return h | h << 16;
}
__device__ __forceinline__ uint32_t hfma2(uint32_t a, uint32_t b, uint32_t c) {
  uint32_t d;
  asm("fma.rn.f16x2 %0, %1, %2, %3;" : "=r"(d) : "r"(a), "r"(b), "r"(c));
  return d;
}
__device__ __forceinline__ uint32_t bmul2(uint32_t a, uint32_t b) {
  uint32_t d;
  asm("mul.rn.bf16x2 %0, %1, %2;" : "=r"(d) : "r"(a), "r"(b));
  return d;
}
__device__ __forceinline__ uint32_t bmul2_abs(uint32_t a, uint32_t b) {
  uint32_t d;
  asm("{\n.reg .b32 t;\nabs.bf16x2 t, %1;\nmul.rn.bf16x2 %0, t, %2;\n}" : "=r"(d) : "r"(a), "r"(b));
  return d;
}
__device__ __forceinline__ uint2 fma4(uint32_t k, const uint2& a, const uint2& c) { return make_uint2(hfma2(k, a.x, c.x), hfma2(k, a.y, c.y)); }
__device__ __forceinline__ uint32_t pack_bf16(float lo, float hi) {
  uint32_t d;
  asm("cvt.rn.bf16x2.f32 %0, %1, %2;" : "=r"(d) : "f"(hi), "f"(lo));
  return d;
}
__device__ __forceinline__ uint32_t pack_f16(float lo, float hi) {
  uint32_t d;
  asm("cvt.rn.f16x2.f32 %0, %1, %2;" : "=r"(d) : "f"(hi), "f"(lo));
  return d;
}

template <int AOFF, int BOFF>
__device__ __forceinline__ void wgmma192(uint32_t (&d)[48], uint64_t da, uint64_t db, uint32_t scale_d) {
  asm volatile(
      "{\n.reg .pred p;\n.reg .b64 qa, qb;\n"
      "setp.ne.b32 p, %50, 0;\n"
      "add.s64 qa, %48, %51;\nadd.s64 qb, %49, %52;\n"
      "wgmma.mma_async.sync.aligned.m64n192k16.f16.f16.f16 "
      "{%0, %1, %2, %3, %4, %5, %6, %7, %8, %9, %10, %11, %12, %13, %14, %15, "
      "%16, %17, %18, %19, %20, %21, %22, %23, %24, %25, %26, %27, %28, %29, %30, %31, "
      "%32, %33, %34, %35, %36, %37, %38, %39, %40, %41, %42, %43, %44, %45, %46, %47}, "
      "qa, qb, p, 1, 1, 0, 0;\n}\n"
      : "+r"(d[0]), "+r"(d[1]), "+r"(d[2]), "+r"(d[3]), "+r"(d[4]), "+r"(d[5]), "+r"(d[6]), "+r"(d[7]), "+r"(d[8]),
        "+r"(d[9]), "+r"(d[10]), "+r"(d[11]), "+r"(d[12]), "+r"(d[13]), "+r"(d[14]), "+r"(d[15]), "+r"(d[16]),
        "+r"(d[17]), "+r"(d[18]), "+r"(d[19]), "+r"(d[20]), "+r"(d[21]), "+r"(d[22]), "+r"(d[23]), "+r"(d[24]),
        "+r"(d[25]), "+r"(d[26]), "+r"(d[27]), "+r"(d[28]), "+r"(d[29]), "+r"(d[30]), "+r"(d[31]), "+r"(d[32]),
        "+r"(d[33]), "+r"(d[34]), "+r"(d[35]), "+r"(d[36]), "+r"(d[37]), "+r"(d[38]), "+r"(d[39]), "+r"(d[40]),
        "+r"(d[41]), "+r"(d[42]), "+r"(d[43]), "+r"(d[44]), "+r"(d[45]), "+r"(d[46]), "+r"(d[47])
      : "l"(da), "l"(db), "r"(scale_d), "n"(AOFF >> 4), "n"(BOFF >> 4));
}
__device__ __forceinline__ void wg_fence() { asm volatile("wgmma.fence.sync.aligned;" ::: "memory"); }
__device__ __forceinline__ void wg_commit() { asm volatile("wgmma.commit_group.sync.aligned;" ::: "memory"); }
template <int N>
__device__ __forceinline__ void wg_wait() { asm volatile("wgmma.wait_group.sync.aligned %0;" ::"n"(N) : "memory"); }
__device__ __forceinline__ void reg_fence(uint32_t (&d)[48]) {
#pragma unroll
  for (int i = 0; i < 48; i++) asm volatile("" : "+r"(d[i])::"memory");
}

constexpr uint32_t X_EXP = 17;
constexpr uint32_t X_LIM = ((15 + 8) << 7) - 1;
constexpr uint32_t U_LIM = ((15 + 6) << 10) - 1;
constexpr uint32_t Y_MIN = 0x3C00, Y_INF = 0x7C00;
constexpr uint32_t NAN2 = 0x7FFF7FFFu;
using Sample = uint4;
__device__ __forceinline__ uint4 ldg128(const uint4* p) {
  uint4 v;
  asm volatile("ld.global.v4.u32 {%0,%1,%2,%3}, [%4];" : "=r"(v.x), "=r"(v.y), "=r"(v.z), "=r"(v.w) : "l"(p));
  return v;
}
__device__ __forceinline__ Sample sample_w(const __nv_bfloat16* w, int lane) {
  const int q = lane >> 3;
  return ldg128((const uint4*)(w + ((q == 0 ? 1 : q == 1 ? 3 : 4) * CH + 47 * q) * CH + 64 * (q % 3)) + (lane & 7));
}
__device__ __forceinline__ Sample sample_x(const __nv_bfloat16* x, int r, int lane) {
  return ldg128((const uint4*)(x + (size_t)(((r >> 3) * 8 + 1 + lane % 6) * IMG + (r & 7) * 64 + 2 * lane) * CH) + lane % 24);
}
__device__ __forceinline__ uint32_t sample_exp(const Sample& s) {
  const uint32_t m = __vmaxu2(__vimax3_u16x2(s.x & NAN2, s.y & NAN2, s.z & NAN2), s.w & NAN2);
  return __reduce_max_sync(0xffffffffu, max(m & 0xFFFFu, m >> 16)) >> 7;
}

constexpr int NP = 16, NTASK = 24 * 36, NROUND = (NTASK + 8 * NP - 1) / (8 * NP);
__host__ __device__ constexpr int stage_end(int k) { return k == 0 ? 1 : k == 1 ? 3 : NROUND; }
__host__ __device__ constexpr int stage_first(int k) {
  for (int i = 0; i < NSTEP; i++) {
    const int h = step_p(i) / 3, n = step_n(i), g = n < 3 ? 3 * h + n : 2 * n + h;
    if ((g + 1) * 36 > stage_end(k - 1) * 8 * NP) return i;
  }
  return -1;
}
static_assert(stage_first(1) >= NU && stage_first(2) > stage_first(1), "stages");
__host__ __device__ constexpr int early(int p) {
  int c = 0;
  while (find_step(p, c) < PIV2) c++;
  return c;
}
struct Task {
  uint32_t n, s, kh, k;
  bool h;
  __device__ __forceinline__ Task(uint32_t t, int lane) {
    const uint32_t grp = t / 36, sub = t % 36;
    n = grp < 6 ? grp % 3 : grp >> 1;
    h = grp < 6 ? grp >= 3 : grp & 1;
    s = sub / 12, kh = (sub / 6) & 1, k = sub % 6 * 32 + lane;
  }
};
constexpr int WTASK = 24 * 64;
__device__ __forceinline__ void prep_load(uint32_t dst, const __nv_bfloat16* __restrict__ w, uint32_t t, int lane) {
  const Task q(min(t, NTASK - 1), 0);
  w += ((q.s * 24 + 2 * q.n + q.kh) * 8 + (lane >> 2)) * CH + q.k + (lane & 3) * 8;
#pragma unroll
  for (int r = 0; r < 3; r++)
    asm volatile("cp.async.cg.shared.global [%0], [%1], 16;" ::"r"(dst + r * 512 + lane * 16), "l"(w + r * 3 * CH * CH) : "memory");
}
__device__ __forceinline__ void prep_store(const float (&g)[3][8], uint4* u, uint32_t t, int lane) {
  const Task q(t, lane);
  const uint32_t n = q.n, s = q.s, kh = q.kh, k = q.k;
  const bool h = q.h;
  const uint32_t jn = (k >> 5) * 4 + ((k >> 1) & 3), row = ((k >> 3) & 3) * 2 + (k & 1);
  u += (((h ? 3 * NSUB : 0) + n) * USLAB + s * UTILE + jn * 256 + kh * 128 + row * 16) >> 4;
  constexpr float nA = -1.f / (2.f * A2 * DD), nB = 1.f / (2.f * B2 * DD);
  constexpr float f0 = nA / S1, f1 = nA / S2, f2 = nB / S3_B, f3 = nB / S4_B;
  const float f4 = n < early(4) ? 1.f / (A2 * B2 * S3_Z0) : 1.f / (A2 * B2), f5 = n < early(5) ? 1.f / S4_I0 : 1.f;
  const float co[3][3] = {{h ? f3 : f0, h ? -PB * f3 : PA * f0, h ? B2 * f3 : A2 * f0},
                          {h ? f4 : f1, h ? 0.f : -PA * f1, h ? 0.f : A2 * f1},
                          {h ? 0.f : f2, h ? 0.f : PB * f2, h ? f5 : B2 * f2}};
#pragma unroll
  for (int p = 0; p < 3; p++) {
    uint32_t o[4];
#pragma unroll
    for (int e = 0; e < 4; e++) {
      float v[2];
#pragma unroll
      for (int q = 0; q < 2; q++) {
        v[q] = co[p][0] * g[0][2 * e + q] + co[p][1] * g[1][2 * e + q] + co[p][2] * g[2][2 * e + q];
        v[q] = __uint_as_float((__float_as_uint(v[q]) + (1u << (12 + 3))) & ~((1u << (13 + 3)) - 1));
      }
      o[e] = pack_f16(v[0], v[1]);
    }
    constexpr uint32_t lim = U_LIM * 0x10001u;
    if (__vimax3_u16x2(__vimax3_u16x2(lim, o[0] & NAN2, o[1] & NAN2), o[2] & NAN2, o[3] & NAN2) != lim) o[0] = NAN2;
    asm volatile("{\n.reg .pred p;\nsetp.lt.u32 p, %5, %6;\n@p st.global.v4.u32 [%0], {%1,%2,%3,%4};\n}" ::"l"(u + p * NSUB * USLAB / 16), "r"(o[0]),
                 "r"(o[1]), "r"(o[2]), "r"(o[3]), "r"(t), "n"(NTASK) : "memory");
  }
}

constexpr int ROWB = IMG * CH * 2;

__device__ __forceinline__ int region_px(int r) { return (r >> 3) * 8 * IMG + (r & 7) * 64; }

__device__ __noinline__ void direct_patch(const __nv_bfloat16* __restrict__ x, const __nv_bfloat16* __restrict__ w,
                                          __nv_bfloat16* __restrict__ out, int y0, int x0, int lane) {
#pragma unroll 1
  for (int t = 0; t < 8; t++) {
    const int oy = y0 + (t >> 1), ox = x0 + (t & 1) * 8;
    float acc[8][6] = {};
#pragma unroll 1
    for (int rs = 0; rs < 9; rs++) {
      const int iy = oy + rs / 3 - 1, ix = ox + rs % 3 - 1;
      if (iy < 0 || iy >= IMG) continue;
#pragma unroll 1
      for (int c = 0; c < CH; c += 2) {
        uint32_t xv[8], wv[2][3];
#pragma unroll
        for (int p = 0; p < 8; p++)
          xv[p] = (unsigned)(ix + p) < IMG ? *(const uint32_t*)(x + ((size_t)iy * IMG + ix + p) * CH + c) : 0u;
#pragma unroll
        for (int e = 0; e < 2; e++)
#pragma unroll
          for (int m = 0; m < 3; m++) wv[e][m] = *(const uint32_t*)(w + (rs * CH + c + e) * CH + 64 * m + 2 * lane);
#pragma unroll
        for (int p = 0; p < 8; p++)
#pragma unroll
          for (int e = 0; e < 2; e++) {
            const float a = __uint_as_float(e ? xv[p] & 0xFFFF0000u : xv[p] << 16);
#pragma unroll
            for (int m = 0; m < 3; m++) {
              acc[p][2 * m] = fmaf(a, __uint_as_float(wv[e][m] << 16), acc[p][2 * m]);
              acc[p][2 * m + 1] = fmaf(a, __uint_as_float(wv[e][m] & 0xFFFF0000u), acc[p][2 * m + 1]);
            }
          }
      }
    }
#pragma unroll
    for (int p = 0; p < 8; p++)
#pragma unroll
      for (int m = 0; m < 3; m++)
        *(uint32_t*)(out + ((size_t)oy * IMG + ox + p) * CH + 64 * m + 2 * lane) = pack_bf16(acc[p][2 * m], acc[p][2 * m + 1]);
  }
}

struct Descs { uint64_t a[2][6], b[NSTEP / NU], pad[8]; };
__host__ __device__ constexpr int slot_use(int i) {
  int c = 0;
  for (int j = 0; j < i; j++) c += vslot(step_p(j), step_n(j)) == vslot(step_p(i), step_n(i));
  return c;
}

__host__ __device__ constexpr int out_time(int q) {
  constexpr int t[24] = {49, 50, 51, 53, 54, 55, 57, 58, 59, 61, 62, 63, 65, 66, 67, 69, 70, 71, 73, 74, 75, 77, 78, 79};
  return t[q];
}
__host__ __device__ constexpr int out_at(int t) {
  for (int q = 0; q < 24; q++)
    if (out_time(q) % NSTEP == t) return q;
  return -1;
}
__host__ __device__ constexpr bool out_ok() {
  for (int q = 0; q < 24; q++)
    if (out_time(q) <= last_on(q / 6) || out_time(q) < PIV2 + (q < 12 ? 4 : 6) || out_time(q) >= first_on(q / 6) + NSTEP ||
        (q && out_time(q) <= out_time(q - 1)))
      return false;
  return true;
}
static_assert(out_ok(), "output plan");
constexpr int OUT_END = out_time(23) + 1 - NSTEP;

struct Consumer {
  uint32_t c1[48], c2[48], c3[48], c4[48];
  const uint64_t *descA, *descB;
  static constexpr uint32_t sb = SMEM_BASE;
  uint8_t* pout;
  int bid, nblk, nlong;
  uint32_t done;
  uint32_t osc, ymax, redo;
  bool lead, ok, odd;

  uint32_t one, zero;
  __device__ __forceinline__ bool always() {
    uint32_t v = one;
    asm volatile("" : "+r"(v));
    return v != 0;
  }
  __device__ __forceinline__ void axpy(uint32_t (&a)[48], uint32_t k, uint32_t (&b)[48]) {
    if (always()) {
      reg_fence(a); reg_fence(b);
#pragma unroll
      for (int i = 0; i < 48; i++) {
        a[i] = hfma2(k, b[i], a[i]);
        if (i % 12 == 11) {
          asm volatile("" : "+r"(a[i])::"memory");
          sched_barrier();
        }
      }
      reg_fence(a);
    }
  }
  uint32_t pa[4], pb[4], px[4];
  __device__ __forceinline__ uint32_t to_bf16(uint32_t h) {
    float lo, hi;
    asm("{\n.reg .b16 l, h;\n.reg .b32 m;\nmov.b32 {l, h}, %3;\ncvt.f32.f16 %0, l;\ncvt.f32.f16 %1, h;\n"
        "abs.f16x2 m, %3;\nmax.NaN.f16x2 %2, m, %2;\n}\n" : "=f"(lo), "=f"(hi), "+r"(ymax) : "r"(h));
    return bmul2(pack_bf16(lo, hi), osc);
  }
  template <int Q, int EXTRA>
  __device__ __forceinline__ void stg(const uint32_t (&v)[4], uint32_t on) {
    constexpr int y = Q < 6 ? 1 : Q < 12 ? 2 : Q < 18 ? 0 : 3;
    asm volatile("{\n.reg .pred p;\nsetp.ne.u32 p, %5, 0;\n@p st.global" ".cs" ".v4.u32 [%0+%6], {%1,%2,%3,%4};\n}\n" ::"l"(pout), "r"(v[0]),
                 "r"(v[1]), "r"(v[2]), "r"(v[3]), "r"(on), "n"(y * ROWB + (Q / 3) % 2 * 8 * (CH * 2) + Q % 3 * 128 + EXTRA) : "memory");
  }
  template <int QW, int QR, bool PIN>
  __device__ __forceinline__ void output(uint32_t on) {
    uint32_t u[4], v[4], t[4];
    if constexpr (PIN) sched_barrier();
    if constexpr (QW >= 0) {
#pragma unroll
      for (int e = 0; e < 4; e++) {
        u[e] = odd ? px[e] : pa[e];
        v[e] = odd ? pb[e] : px[e];
      }
    }
    if constexpr (QR >= 0) {
      const uint32_t(&d)[48] = QR < 6 ? c1 : QR < 12 ? c2 : QR < 18 ? c3 : c4;
      constexpr int o = 16 * (QR % 3) + (QR / 3) % 2;
#pragma unroll
      for (int e = 0; e < 4; e++) {
        if constexpr (PIN) { if (e % 2 == 0) sched_barrier(); }
        pa[e] = to_bf16(d[o + 2 * e]);
        pb[e] = to_bf16(d[o + 8 + 2 * e]);
        t[e] = odd ? pa[e] : pb[e];
      }
    }
    if constexpr (PIN) asm volatile("{\n.reg .pred p;\nsetp.ne.u32 p, %0, 0;\n@p pmevent 0;\n}" ::"r"((uint32_t)ok) : "memory");
    if constexpr (PIN) sched_barrier();
    if constexpr (QW >= 0) { stg<QW, 0>(u, on); stg<QW, CH * 2>(v, on); }
    if constexpr (QR >= 0) {
#pragma unroll
      for (int e = 0; e < 4; e++) px[e] = __shfl_xor_sync(0xffffffffu, t[e], 4);
    }
    if constexpr (PIN) sched_barrier();
  }
  __device__ __forceinline__ void range_check() {
    const uint32_t m = __reduce_max_sync(0xffffffffu, max(ymax & 0xFFFFu, ymax >> 16));
    redo |= (uint32_t)(m - Y_MIN >= Y_INF - Y_MIN) << done;
    ymax = 0;
  }
  template <int Q>
  __device__ __forceinline__ void flush() {
    if constexpr (Q <= 24) {
      output<(Q > 0 && out_time(Q > 0 ? Q - 1 : 0) >= NSTEP - 1 ? Q - 1 : -1), (Q < 24 && out_time(Q % 24) >= NSTEP ? Q : -1), false>(1);
      flush<Q + 1>();
    }
  }
  template <int I>
  __device__ __forceinline__ void hook() {
    constexpr float LP = PB * (PB - PA) / (2.f * A2), LM = PB * (PB + PA) / (2.f * A2);
    constexpr int QW = out_at((I + NSTEP - 1) % NSTEP), QR = out_at(I);
    if constexpr (QW >= 0 || QR >= 0) output<QW, QR, true>(I > OUT_END ? 1u : done);
    if constexpr (I == 20) {
      static_assert(OUT_END < 20, "pointer update");
      range_check();
      osc = lds32(sb + OFF_OSC);
      const int r = bid + done * nblk, d = region_px(r & 0xffff) - (done ? region_px((r - nblk) & 0xffff) : region_px(r - nblk));
      asm volatile("mad.wide.s32 %0, %1, 384, %0;" : "+l"(pout) : "r"(d));
    }
    if constexpr (I == 42) { if (bid >= nlong && done == 0) spin_cycles(29000); }
    if constexpr (I == PIV2) axpy(c1, h2const(S3_B * (B2 / A2) / S1), c3);
    if constexpr (I == PIV2) axpy(c2, h2const(S3_B * (B2 / A2) / S2), c3);
    if constexpr (I == PIV2 + 1) axpy(c4, h2const(-S3_B / S4_B), c3);
    if constexpr (I == PIV2 + 1) axpy(c1, h2const(S4_B * LP / S1), c4);
    if constexpr (I == PIV2 + 2) axpy(c2, h2const(S4_B * LM / S2), c4);
    if constexpr (I == PIV2 + 2) axpy(c3, h2const(S4_B * (-DD / A2)), c4);
    if constexpr (I == PIV2 + 3) { axpy(c1, h2const(-1.f / (2.f * PA)), c2); axpy(c2, h2const(PA), c1); }
    if constexpr (I == PIV2 + 4) axpy(c4, h2const(A2), c1);
    if constexpr (I == PIV2 + 5) axpy(c3, h2const(1.f / A2), c2);
  }

  template <int I>
  __device__ __forceinline__ void steps() {
    if constexpr (I < NSTEP) {
      uint32_t(&d)[48] = step_acc(I) == 0 ? c1 : step_acc(I) == 1 ? c2 : step_acc(I) == 2 ? c3 : c4;
      constexpr int vo = vslot(step_p(I), step_n(I)) * VSLOT, uo = (I % NU) * USLAB;
      constexpr int J = (I + 1) % NSTEP;
      if (!ok) {
        mbar_wait_short(sb + BAR_UFULL + 8 * (I % NU), (I / NU) & 1);
        if constexpr (first_use(step_n(I)) == I) mbar_wait_short(sb + BAR_VFULL + 8 * (step_n(I) % NB), step_n(I) / NB);
      }
      const uint64_t da = descA[slot_use(I)], db = descB[I / NU];
      wg_fence();
      wgmma192<vo, uo>(d, da, db, first_on(step_acc(I)) == I ? 0u : 1u);
      wgmma192<vo + 16, uo + UTILE>(d, da, db, 1u);
      wgmma192<vo + 32, uo + 2 * UTILE>(d, da, db, 1u);
      wg_commit();
      ok = mbar_test(sb + BAR_UFULL + 8 * (J % NU), ((J / NU) & 1) ^ zero);
      if constexpr (first_use(step_n(J)) == J) ok &= mbar_test(sb + BAR_VFULL + 8 * (step_n(J) % NB), (step_n(J) / NB) ^ zero);
      hook<I>();
      wg_wait<0>();
      reg_fence(d);
      if (lead) mbar_arrive(sb + BAR_UEMPTY + 8 * (I % NU));
      if constexpr (gate_of(I) >= 0) { if (lead) mbar_arrive(sb + BAR_GATE + 8 * (gate_of(I) % NB)); }
      steps<I + 1>();
    }
  }
};

struct SlotTab { uint32_t off[NSUB][8]; };
constexpr SlotTab make_slots() {
  SlotTab t = {};
  for (int n = 0; n < NSUB; n++)
    for (int p = 0; p < 6; p++) t.off[n][p] = vslot(p, n) * VSLOT;
  return t;
}
__constant__ __align__(64) SlotTab c_slots = make_slots();

constexpr int PF_X = 22, PF_Y = 2;
constexpr int PF_NB = 66 / PF_X * (10 / PF_Y);
static_assert(PF_X * PF_Y * 16 <= 768, "sink");
__host__ __device__ constexpr uint32_t pf_box(int g, int q) {
  return 1u << 31 | (g / 3) << 30 | (g % 3 * 2) << 27 | (q / (10 / PF_Y) * PF_X) << 20 | (q % (10 / PF_Y) * PF_Y) << 16;
}
__host__ __device__ constexpr int slab_of(int i) { return step_p(i % NSTEP) * NSUB + step_n(i % NSTEP); }
struct LoadTab { uint32_t e[2][NSTEP], e2[32], pf0[16]; };
constexpr LoadTab make_loads() {
  LoadTab t = {};
  constexpr int win[6] = {19, 38, 42, 68, 69, 91};
  int when[6 * PF_NB] = {};
  for (int g = 0; g < 3; g++)
    for (int q = 0; q < PF_NB; q++) {
      const int i = win[2 * g] + q * (win[2 * g + 1] - win[2 * g]) / PF_NB;
      t.e[1][i % NSTEP] = pf_box(i < NSTEP ? g + 3 : g, q);
      when[g * PF_NB + q] = i - NSTEP;
      when[(g + 3) * PF_NB + q] = i;
    }
  int h = 2 * 0 * 2;
  for (int k = 240 ? 0 : PF_NB; k < 6 * PF_NB; k++) {
    const uint32_t e = pf_box(k / PF_NB, k % PF_NB) | (k < PF_NB ? 1 << 27 : 0);
    if (k < (240 ? 0 : PF_NB) + 15) { t.pf0[k % PF_NB] = e; continue; }
    if (h < when[k] * 2) h = when[k] * 2;
    const int i = h / 2;
    if (i < NSTEP) (t.e[0][i] ? t.e2[i] : t.e[0][i]) = e;
    h += 2;
  }
  for (int i = 0; i < 2 * NSTEP; i++) t.e[i / NSTEP][i % NSTEP] |= slab_of(i + 10) << 8 | slab_of(i + NU);
  return t;
}
__constant__ __align__(64) LoadTab c_load = make_loads();

template <int BYTES>
__device__ __forceinline__ uint32_t warm(const void* p, uint32_t zero) {
  uint32_t v = ~0u;
#pragma unroll
  for (int o = 0; o < BYTES; o += 64) v &= ((const uint32_t*)p)[o / 4 + zero];
  return v;
}

__global__ void __launch_bounds__(384, 1) __cluster_dims__(1, 1, 1)
conv_kernel(const __grid_constant__ CUtensorMap tmX, const __grid_constant__ CUtensorMap tmH, const __grid_constant__ CUtensorMap tmP, const __nv_bfloat16* __restrict__ xin, const __nv_bfloat16* __restrict__ wgt,
            __nv_bfloat16* __restrict__ out, uint4* ubuf, uint32_t* arrived, int nblk, int nlong, int nmax, const __grid_constant__ Descs desc) {
  extern __shared__ uint8_t smem_raw[];
  const int tid = threadIdx.x, lane = tid & 31, bid = blockIdx.x;
  const int pidx = bid - (nblk - NP);
  constexpr uint32_t sb = SMEM_BASE;
  uint32_t epoch = 0, t0 = 0;
  if (tid >= 352) {
    asm volatile("prefetch.tensormap [%0];" ::"l"(&tmX) : "memory");
    constexpr uint64_t twos = ((1ull << NU) - 1) << (BAR_UEMPTY - OFF_BAR) / 8 | ((1ull << 2 * NB) - 1) << (BAR_VFULL - OFF_BAR) / 8;
    constexpr uint64_t threes = ((1ull << NB) - 1) << (BAR_VFULL - OFF_BAR) / 8;
    if (lane == 0) {
#pragma unroll
      for (int i = 0; i < NBAR; i++) mbar_init(sb + OFF_BAR + 8 * i, 1 + ((twos >> i) & 1) + ((threes >> i) & 1));
      asm volatile("fence.mbarrier_init.release.cluster;" ::: "memory");
      fence_async();
    }
    __syncwarp();
    cluster_arrive_relaxed();
    epoch = stage_enter(arrived, lane);
    if (pidx >= 0) asm volatile("bar.sync 2, 64;" ::: "memory");
    t0 = now();
#pragma unroll 1
    for (int k = 0, box = 0; k < 9; k++, box = box < 6 ? box + 3 : box - 5) {
      if (pidx < 0) spin_until(t0, 400 + k * 450);
      tma_box_warp(sb + OFF_X + box * XBOX, k < 8 ? &tmX : &tmH, sb + BAR_XFULL + 8 * box, k < 8 ? XBOX : XHBOX, 0, (bid & 7) * 64 - 1 + k * 8,
                   ((bid & 0xffff) >> 3) * 8 - 1);
      if (k == 0) asm volatile("prefetch.tensormap [%0];\nprefetch.tensormap [%1];" ::"l"(&tmH), "l"(&tmP) : "memory");
    }
  } else {
    cluster_arrive_relaxed();
  }
  if (tid < 256) {
    if (pidx >= 0) {
      uint32_t t = pidx * 8 + (tid >> 5);
      uint32_t stage = 0, wsm = sb + OFF_V + (tid >> 5) * NROUND * WTASK;
      prep_load(wsm, wgt, t, lane);
      const Sample ws = sample_w(wgt, lane);
      float sw = 0.f;
#pragma unroll 1
      for (int round = -0; round < NROUND; round++, t += 8 * NP, wsm += WTASK) {
        if (round == 0) sw = __uint_as_float(max(253 - (int)sample_exp(ws), 0) << 23);
        if (round >= 0) asm volatile("cp.async.wait_all;" ::: "memory");
        __syncwarp();
        float g[3][8];
#pragma unroll
        for (int i = 0; i < 24; i++) {
          uint16_t v;
          asm volatile("ld.shared.u16 %0, [%1];" : "=h"(v) : "r"(wsm + i * 64 + lane * 2) : "memory");
          g[i / 8][i % 8] = __uint_as_float((uint32_t)v << 16) * sw;
        }
        prep_store(g, ubuf, t, lane);
        if (round + 1 == stage_end(0) || round + 1 == stage_end(1) || round + 1 == NROUND) {
          asm volatile("bar.sync 1, 256;" ::: "memory");
          const uint32_t inc = pidx ? 1 : 0x80000001u - (stage ? NP : 2 * nblk);
          if (stage == 2) asm volatile("ld.relaxed.gpu.global.u32 %0, [%1];" : "=r"(epoch) : "l"(arrived + 64) : "memory");
          if (tid == 0) asm volatile("red.release.gpu.global.add.u32 [%0], %1;" ::"l"(arrived + 32 * stage), "r"(inc) : "memory");
          asm volatile("bar.sync 1, 256;" ::: "memory");
          if (stage++ == 0) {
#pragma unroll 1
            for (int k = 1; k < NROUND; k++) prep_load(wsm + k * WTASK, wgt, t + k * 8 * NP, lane);
          }
        }
      }
      if (tid < 32) asm volatile("bar.arrive 2, 64;" ::: "memory");
    } else if (tid < 32) {
      t0 = now();
      epoch = stage_enter(arrived, lane);
      spin_until(t0, 2200);
    }
  }
  if (smem_u32(smem_raw) != SMEM_BASE) __trap();
  const int warp = __shfl_sync(0xffffffffu, tid >> 5, 0);

  if (warp < 8) {
    const int wg = warp >> 2;
    if (warp == 7) { spin_until(now(), 2000); if ((warm<sizeof(SlotTab)>(&c_slots, tid >> 10) & warm<sizeof(LoadTab)>(&c_load, tid >> 10)) == ~0u) __trap(); }
    cluster_wait();
    if (warp == 0) {
      stage_wait(arrived, __shfl_sync(0xffffffffu, epoch, 0));
#pragma unroll
      for (int s = 0; s < NU; s++) load_u_warp(sb + OFF_U + s * USLAB, (const uint8_t*)ubuf + slab_of(s) * USLAB, sb + BAR_UFULL + 8 * s);
    }
    asm volatile("setmaxnreg.inc.sync.aligned.u32 224;");
    Consumer c;
#pragma unroll
    for (int i = 0; i < 48; i++) { c.c1[i] = 0; c.c2[i] = 0; c.c3[i] = 0; c.c4[i] = 0; }
#pragma unroll
    for (int e = 0; e < 4; e++) c.pa[e] = c.pb[e] = c.px[e] = 0;
    c.descA = desc.a[wg];
    c.descB = desc.b;
    c.lead = (tid & 127) == 0;
    c.one = __shfl_sync(0xffffffffu, nblk, 0);
    c.zero = __popc(__activemask()) >> 6;
    c.ok = false;
    c.bid = bid;
    c.nblk = nblk;
    c.nlong = nlong;
    c.odd = (lane >> 2) & 1;
    c.pout = (uint8_t*)out + (long long)(region_px(bid - nblk) + wg * 4 * IMG + (warp & 3) * 16 + (lane >> 3) * 2) * (CH * 2) + (lane & 7) * 16;
    c.done = c.osc = c.ymax = c.redo = 0;
#pragma unroll 1
    do {
      wg_wait<0>();
      c.steps<0>();
      c.done++;
    } while (bid + (int)c.done * nblk < NREG);
    c.flush<0>();
    c.range_check();
    if (c.redo >> 1) {
      __syncwarp();
      for (int i = 0; i < (int)c.done; i++)
        if ((c.redo >> (i + 1)) & 1) {
          const int r = bid + i * nblk;
          direct_patch(xin, wgt, out, (r >> 3) * 8 + wg * 4, (r & 7) * 64 + (warp & 3) * 16, lane);
        }
    }
  } else {
    asm volatile("setmaxnreg.dec.sync.aligned.u32 56;");
    const int nitem = nmax - (bid >= nlong);
    if (warp == 11) {
      const uint8_t* ubase = (const uint8_t*)ubuf;
      epoch = __shfl_sync(0xffffffffu, epoch, 0);
      int r = bid, npf = 0;
      auto prefetch = [&](uint32_t e) {
        const int rr = r + ((e >> 30) & 1) * nblk;
        if ((int)e < 0 && rr < NREG) {
          asm volatile("{\n.reg .pred p;\nelect.sync _|p, 0xffffffff;\n"
                       "@p cp.async.bulk.tensor.3d.shared::cluster.global.mbarrier::complete_tx::bytes [%0], [%1, {%3, %4, %5}], [%2];\n}\n" ::"r"(sb + OFF_DUMMY),
                       "l"(&tmP), "r"(sb + BAR_DUMMY), "r"((e >> 22) & 0xE0), "r"((rr & 7) * 64 - 1 + ((e >> 20) & 127)),
                       "r"(((rr & 0xffff) >> 3) * 8 - 1 + ((e >> 16) & 15)) : "memory");
          npf++;
        }
      };
#pragma unroll 1
      for (int q = 0; q < 15; q++) {
        if (pidx < 0) spin_until(t0, 400 + 8 * 450 + 110 + q * 240);
        prefetch(c_load.pf0[q]);
      }
      cluster_wait();
      uint32_t smid;
      asm("mov.u32 %0, %%smid;" : "=r"(smid));
      const uint8_t* uline = (const uint8_t*)ubuf + (bid % (144 / 3) * 3 + lane) * 128;
      const bool uon = bid < 116 / (144 / 3) * (144 / 3);
      uint32_t dst = sb + OFF_U, ebar = sb + BAR_UEMPTY, upar = 0;
      int i = 0, tab = 0;
#pragma unroll 1
      for (int left = nitem * NSTEP - NU; left > 0; left--) {
        const uint32_t e = c_load.e[0][tab + i];
        const uint8_t* src = ubase + (e & 255) * USLAB;
        const uint8_t* pu = uline + ((e >> 8) & 255) * USLAB;
        if (tab + i == stage_first(1) - NU) stage_wait(arrived + 32, epoch);
        if (tab + i == stage_first(2) - NU) stage_wait(arrived + 64, epoch);
        mbar_wait(ebar, upar);
        load_u_warp(dst, src, ebar - (BAR_UEMPTY - BAR_UFULL));
        prefetch(e);
        if (2 > 2 && tab + i < 32) prefetch(c_load.e2[i]);
        if (lane < 3 && uon && tab + i >= NSTEP - 10 && left > 10)
          asm volatile("cp.async.ca.shared.global.L2::128B [%0], [%1], 4;" ::"r"(sb + OFF_DUMMY + 704 + lane * 4), "l"(pu) : "memory");
        if (++i == NSTEP) { i = 0; r += nblk; tab = NSTEP; }
        const int s = i & (NU - 1);
        dst = sb + OFF_U + s * USLAB;
        ebar = sb + BAR_UEMPTY + 8 * s;
        if (s == 0) upar ^= 1;
      }
#pragma unroll 1
      for (int s = 0; s < NU; s++) mbar_wait(sb + BAR_UEMPTY + 8 * s, 1);
      if (lane == 0) asm volatile("mbarrier.arrive.expect_tx.shared::cta.b64 _, [%0], %1;" ::"r"(sb + BAR_DUMMY), "r"(npf * (PF_X * PF_Y * 16)) : "memory");
      mbar_wait(sb + BAR_DUMMY, 0);
      asm volatile("cp.async.wait_all;" ::: "memory");
    } else {
      const int w = warp - 8, col = (lane >> 1) & 7, chunk = lane >> 4;
      const uint32_t xbox = sb + OFF_X + w * 3 * XBOX, xbar = sb + BAR_XFULL + 24 * w;
      const uint32_t xl = xbox + col * 32 + ((chunk ^ (col >> 2)) << 4) + (lane & 1) * 8;
      const uint32_t vl = sb + OFF_V + chunk * VROW + w * 128 + (lane & 15) * 8;
      const bool in_row = w < 2 || col < 2;
      const uint32_t pitch2 = w < 2 ? 256 : 64, bytes2 = 10 * pitch2;
      const uint32_t xl2 = w < 2 ? xl + 2 * XBOX : xbox + 2 * XBOX + (col & 1) * 32 + chunk * 16 + (lane & 1) * 8;
      const CUtensorMap* tm2 = w < 2 ? &tmX : &tmH;
      auto xrow = [&](int j, int i) { return j < 2 ? xl + j * XBOX + i * 256 : xl2 + i * pitch2; };
      auto load_box = [&](int j, uint32_t zero, bool on, int c, int x, int y) {
        if (on) tma_box_warp(xbox + j * XBOX, j < 2 ? &tmX : tm2, xbar + 8 * j, (j < 2 ? XBOX : bytes2) | zero, c, x + j * 24, y);
      };
      const Sample ws = sample_w(wgt, lane), xs = sample_x(xin, bid, lane);
      uint32_t xsc;
      {
        const int ex = sample_exp(xs), eo = ex + (int)sample_exp(ws) - (111 + X_EXP), es = 127 + X_EXP - ex;
        xsc = es >= 1 && eo >= 1 && eo <= 254 ? es * 0x00800080u : NAN2;
        asm volatile("st.shared.u32 [%0], %1;" ::"r"(sb + OFF_OSC), "r"(eo * 0x00800080u) : "memory");
      }
      constexpr uint32_t gate_par = [] { uint32_t m = 0; for (int n = 0; n < NSUB; n++) if ((n / NB) ^ (gate(n % NB) < 0)) m |= 1u << n; return m; }();
      constexpr uint32_t LIM2 = X_LIM * 0x10001u;
      cluster_wait();
      auto conv = [&](uint2& v, uint32_t m) {
        const uint32_t tx = bmul2(v.x, xsc), ty = bmul2(v.y, xsc), ux = tx & NAN2, uy = ty & NAN2;
        v = make_uint2(ux * 7 + tx, uy * 7 + ty);
        return __vimax3_u16x2(m, ux, uy);
      };
      uint32_t so[6] = {};
      auto planes = [&](const uint2* h, uint32_t m, uint32_t a, bool on) {
        constexpr uint32_t NB2 = h2const(-B2), NA2 = h2const(-A2);
        const uint2 e1 = fma4(NB2, h[2], h[4]), e2 = fma4(NA2, h[2], h[4]);
        sts64(a + so[4], fma4(NA2, fma4(NB2, h[0], h[2]), e1), on);
        const uint2 o1 = fma4(NB2, h[1], h[3]), o2 = fma4(NA2, h[1], h[3]);
        sts64(a + so[5], fma4(NA2, o1, fma4(NB2, h[3], h[5])), on);
        uint2 v = fma4(h2const(PA), o1, e1);
        if (m != LIM2) v.x = NAN2;
        sts64(a + so[0], v, on);
        sts64(a + so[1], fma4(h2const(-PA), o1, e1), on);
        sts64(a + so[2], fma4(h2const(PB), o2, e2), on);
        sts64(a + so[3], fma4(h2const(-PB), o2, e2), on);
      };
      int r = bid, n = 0;
      uint32_t par = 0;
#pragma unroll 1
      for (int left = nitem * NSUB; left > 0; left--) {
        const int nb = n >= NB ? n - NB : n;
        const bool refill = left > 1;
        uint2 d[10];
        mbar_wait(xbar, par);
#pragma unroll
        for (int i = 0; i < 6; i++) d[i] = lds64(xrow(0, i));
#pragma unroll
        for (int p = 0; p < 6; p++) so[p] = c_slots.off[n][p];
        const uint32_t gpar = (gate_par >> n) & 1;
        if (++n == NSUB) { n = 0; r += nblk; }
        const int fc = n * 16, fx = (r & 7) * 64 - 1 + w * 8, fy = ((r & 0xffff) >> 3) * 8 - 1;
#pragma unroll
        for (int j = 0; j < 3; j++) {
          const bool on = j < 2 || in_row;
#pragma unroll
          for (int i = 6; i < 10; i++) d[i] = lds64(xrow(j, i));
          const bool xok = j < 2 && mbar_test(xbar + 8 * (j + 1), par);
          sched_barrier();
          const uint32_t m45 = conv(d[5], conv(d[4], LIM2));
          const uint32_t ma = conv(d[3], conv(d[1], conv(d[0], conv(d[2], m45))));
          if (j == 0) { mbar_wait(sb + BAR_GATE + 8 * nb, gpar); }
          planes(d, ma, vl + j * 384, on);
          sched_barrier();
          const uint32_t mb = conv(d[9], conv(d[7], conv(d[6], conv(d[8], m45))));
          load_box(j, mb & 0x8000u, refill, fc, fx, fy);
          uint2 h[6];
#pragma unroll
          for (int i = 0; i < 6; i++) h[i] = d[4 + i];
          if (j < 2) {
            mbar_wait(xbar + 8 * (j + 1), par, xok);
#pragma unroll
            for (int i = 0; i < 6; i++) d[i] = lds64(xrow(j + 1, i));
          }
          sched_barrier();
          planes(h, mb, vl + j * 384 + VPIECE, on);
          sched_barrier();
        }
        fence_async();
        asm volatile("{\n.reg .pred p;\nelect.sync _|p, 0xffffffff;\n@p mbarrier.arrive.shared::cta.b64 _, [%0];\n}\n" ::"r"(sb + BAR_VFULL + 8 * nb) : "memory");
        par ^= 1;
      }
    }
  }
}

constexpr uint64_t make_desc(uint32_t off, uint32_t lbo, uint32_t sbo) {
  return (uint64_t)((SMEM_BASE + off) >> 4) | ((uint64_t)(lbo >> 4) << 16) | ((uint64_t)(sbo >> 4) << 32);
}

typedef CUresult (*EncodeFn)(CUtensorMap*, CUtensorMapDataType, cuuint32_t, void*, const cuuint64_t*, const cuuint64_t*,
                             const cuuint32_t*, const cuuint32_t*, CUtensorMapInterleave, CUtensorMapSwizzle,
                             CUtensorMapL2promotion, CUtensorMapFloatOOBfill);

}

extern "C" void kernel_launch(void* const* d_in, const int* in_sizes, int n_in, void* d_out, int out_size) {
  static EncodeFn enc = nullptr;
  static int nblk = 0;
  static uint4* ubuf;
  static uint32_t* arrived;
  if (!enc) {
    cudaGetSymbolAddress((void**)&ubuf, g_U);
    cudaGetSymbolAddress((void**)&arrived, g_arrived);
    cudaDriverEntryPointQueryResult qr;
    cudaGetDriverEntryPoint("cuTensorMapEncodeTiled", (void**)&enc, cudaEnableDefault, &qr);
    cudaFuncSetAttribute(conv_kernel, cudaFuncAttributeMaxDynamicSharedMemorySize, SMEM_BYTES);
    int dev;
    cudaGetDevice(&dev);
    cudaDeviceGetAttribute(&nblk, cudaDevAttrMultiProcessorCount, dev);
  }
  CUtensorMap tmX, tmH, tmP;
  const cuuint64_t dims[3] = {CH, IMG, IMG};
  const cuuint64_t strides[2] = {CH * 2, (cuuint64_t)CH * 2 * IMG};
  const cuuint32_t es[3] = {1, 1, 1};
  const cuuint32_t boxX[3] = {16, 8, 10}, boxH[3] = {16, 2, 10}, boxP[3] = {8, PF_X, PF_Y};
  enc(&tmH, CU_TENSOR_MAP_DATA_TYPE_BFLOAT16, 3, d_in[0], dims, strides, boxH, es, CU_TENSOR_MAP_INTERLEAVE_NONE,
      CU_TENSOR_MAP_SWIZZLE_NONE, CU_TENSOR_MAP_L2_PROMOTION_L2_64B, CU_TENSOR_MAP_FLOAT_OOB_FILL_NONE);
  enc(&tmP, CU_TENSOR_MAP_DATA_TYPE_BFLOAT16, 3, d_in[0], dims, strides, boxP, es, CU_TENSOR_MAP_INTERLEAVE_NONE,
      CU_TENSOR_MAP_SWIZZLE_NONE, CU_TENSOR_MAP_L2_PROMOTION_L2_128B, CU_TENSOR_MAP_FLOAT_OOB_FILL_NONE);
  enc(&tmX, CU_TENSOR_MAP_DATA_TYPE_BFLOAT16, 3, d_in[0], dims, strides, boxX, es, CU_TENSOR_MAP_INTERLEAVE_NONE,
      CU_TENSOR_MAP_SWIZZLE_32B, CU_TENSOR_MAP_L2_PROMOTION_L2_64B, CU_TENSOR_MAP_FLOAT_OOB_FILL_NONE);
  Descs desc = {};
  for (int i = 0; i < 6; i++) { desc.a[0][i] = make_desc(OFF_V, VROW, 128); desc.a[1][i] = make_desc(OFF_V + VPIECE, VROW, 128); }
  for (int i = 0; i < NSTEP / NU; i++) desc.b[i] = make_desc(OFF_U, 128, 256);
  conv_kernel<<<nblk, 384, SMEM_BYTES>>>(tmX, tmH, tmP, (const __nv_bfloat16*)d_in[0], (const __nv_bfloat16*)d_in[1], (__nv_bfloat16*)d_out, ubuf, arrived, nblk,
                                         NREG % nblk ? NREG % nblk : nblk, (NREG + nblk - 1) / nblk, desc);
}
```

```cpp
#include <cuda_runtime.h>
#include <cuda_bf16.h>
#include <cuda.h>
#include <stdint.h>

namespace {

constexpr int IMG = 512, CH = 192;
constexpr float PA = 0.6875f, PB = 1.5f;
constexpr float A2 = PA * PA, B2 = PB * PB, DD = B2 - A2;

constexpr int NSTEP = 72, NSUB = 12;
__host__ __device__ constexpr int sched(int i) {
  constexpr int t[NSTEP] = {
      0x00, 0x10, 0x20, 0x01, 0x11, 0x21, 0x02, 0x12, 0x22, 0x30, 0x31, 0x32, 0x23, 0x33, 0x03, 0x13, 0x24, 0x34,
      0x04, 0x14, 0x25, 0x35, 0x05, 0x15, 0x26, 0x36, 0x06, 0x16, 0x27, 0x37, 0x07, 0x17, 0x28, 0x38, 0x08, 0x18,
      0x29, 0x39, 0x09, 0x19, 0x2a, 0x3a, 0x0a, 0x1a, 0x2b, 0x3b, 0x1b, 0x0b, 0x40, 0x41, 0x50, 0x42, 0x51, 0x43,
      0x44, 0x52, 0x45, 0x46, 0x53, 0x47, 0x48, 0x49, 0x4a, 0x4b, 0x54, 0x55, 0x56, 0x57, 0x58, 0x59, 0x5a, 0x5b};
  return t[i];
}
__host__ __device__ constexpr int step_p(int i) { return sched(i) >> 4; }
__host__ __device__ constexpr int step_n(int i) { return sched(i) & 15; }
__host__ __device__ constexpr int step_acc(int i) { return step_p(i) < 4 ? step_p(i) : step_p(i) - 2; }
__host__ __device__ constexpr int first_on(int acc) {
  for (int i = 0; i < NSTEP; i++)
    if (step_acc(i) == acc) return i;
  return -1;
}
__host__ __device__ constexpr int last_on(int acc) {
  for (int i = NSTEP - 1; i >= 0; i--)
    if (step_acc(i) == acc) return i;
  return -1;
}
__host__ __device__ constexpr int find_step(int p, int n) {
  for (int i = 0; i < NSTEP; i++)
    if (sched(i) == p * 16 + n) return i;
  return -1;
}
__host__ __device__ constexpr int first_use(int n) {
  for (int i = 0; i < NSTEP; i++)
    if (step_n(i) == n) return i;
  return -1;
}
constexpr float S1 = 1.f / PA, S2 = 1.f / (2.f * A2), S3 = -A2 / (2.f * DD), S4 = -1.f / (PB * DD);
constexpr int PIV = find_step(3, NSUB - 1);
static_assert(find_step(2, NSUB - 1) == PIV - 1 && last_on(1) == PIV + 1 && last_on(0) == PIV + 2 && PIV + 3 == 4 * NSUB &&
              step_p(PIV + 3) == 4 && step_p(PIV + 4) == 4 && step_p(PIV + 5) == 5, "basis change");

constexpr int NV = 32, NB = 6;
__host__ __device__ constexpr int vslot(int p, int n) {
  constexpr int t[6][NSUB] = {
      {23, 22, 10, 9, 12, 23, 30, 14, 24, 27, 28, 27}, {30, 4, 14, 28, 24, 27, 19, 25, 23, 30, 23, 26}, {24, 6, 27,
      15, 16, 10, 26, 15, 17, 22, 25, 30}, {25, 26, 8, 13, 17, 22, 28, 22, 26, 19, 24, 22}, {20, 29, 21, 2, 4, 6, 8,
      10, 12, 14, 16, 18}, {31, 0, 1, 3, 5, 7, 9, 11, 13, 15, 17, 19}};
  return t[p][n];
}
__host__ __device__ constexpr int gate(int n) {
  constexpr int t[NSUB] = {-21, -15, -9, -2, 5, 11, 16, 21, 26, 30, 35, 39};
  return t[n];
}
__host__ __device__ constexpr int gate_of(int i) {
  for (int n = 0; n < NSUB; n++)
    if ((gate(n) + NSTEP) % NSTEP == i) return n;
  return -1;
}
__host__ __device__ constexpr bool gates_ok() {
  for (int n = 0; n < NSUB; n++) {
    for (int p = 0; p < 6; p++)
      for (int d = 1; d <= NSUB; d++)
        for (int q = 0; q < 6; q++) {
          const int m = (n - d + NSUB) % NSUB;
          if (vslot(q, m) == vslot(p, n) && (find_step(q, m) - (n - d < 0 ? NSTEP : 0) > gate(n) || (m == n && p != q))) return false;
        }
    if (n > 0 && (gate(n) <= gate(n - 1) || first_use(n) <= first_use(n - 1))) return false;
    if (gate(n) >= first_use(n)) return false;
    if (gate((n + NB) % NSUB) + (n >= NB ? NSTEP : 0) < first_use(n)) return false;
  }
  return gate(0) + NSTEP > gate(NSUB - 1) && gate(NB) >= 0;
}
static_assert(gates_ok(), "gates");

constexpr int UTILE = CH * 16 * 2;
constexpr int USLAB = 3 * UTILE;
constexpr int NU = 4;
constexpr int VROW = 66 * 16;
constexpr int VPIECE = 2 * VROW;
constexpr int VSLOT = 2 * VPIECE;
constexpr int XBOX = 10 * 8 * 32;
constexpr int XHBOX = 10 * 2 * 32;
static_assert(NSTEP % (2 * NU) == 0, "static ring parity");

constexpr int OFF_X = 0;
constexpr int OFF_SINK = OFF_X + 8 * XBOX + XHBOX;
constexpr int OFF_U = OFF_SINK + 768;
constexpr int OFF_V = OFF_U + NU * USLAB;
constexpr int OFF_BAR = OFF_V + NV * VSLOT;
constexpr int BAR_UFULL = OFF_BAR;
constexpr int BAR_UEMPTY = BAR_UFULL + 8 * NU;
constexpr int BAR_XFULL = BAR_UEMPTY + 8 * NU;
constexpr int BAR_VFULL = BAR_XFULL + 8 * 9;
constexpr int BAR_GATE = BAR_VFULL + 8 * NB;
constexpr int BAR_SINK = BAR_GATE + 8 * NB;
constexpr int OFF_OSC = BAR_SINK + 8;
constexpr int NBAR = (OFF_OSC - OFF_BAR) / 8;
constexpr int SMEM_BYTES = OFF_OSC + 8;
constexpr uint32_t SMEM_BASE = 1024;
static_assert(SMEM_BYTES <= 232448, "smem");

constexpr int NREG = 512;

__device__ __align__(128) uint4 g_U[NSTEP * USLAB / 16];
__device__ uint32_t g_arrived[3 * 32];

__device__ __forceinline__ uint32_t smem_u32(const void* p) { return (uint32_t)__cvta_generic_to_shared(p); }
__device__ __forceinline__ void mbar_init(uint32_t a, int c) {
  asm volatile("mbarrier.init.shared::cta.b64 [%0], %1;" ::"r"(a), "r"(c) : "memory");
}
__device__ __forceinline__ void mbar_arrive(uint32_t a) {
  asm volatile("mbarrier.arrive.shared::cta.b64 _, [%0];" ::"r"(a) : "memory");
}
__device__ __forceinline__ void mbar_wait(uint32_t a, uint32_t parity, uint32_t skip = 0) {
  asm volatile(
      "{\n"
      ".reg .pred p;\n"
      ".reg .u32 n;\n"
      "setp.ne.u32 p, %2, 0;\n"
      "@p bra.uni LAB_DONE;\n"
      "mov.u32 n, 0;\n"
      "LAB_WAIT:\n"
      "mbarrier.try_wait.parity.shared::cta.b64 p, [%0], %1;\n"
      "@p bra.uni LAB_DONE;\n"
      "add.u32 n, n, 1;\n"
      "setp.lt.u32 p, n, 4000000;\n"
      "@p bra.uni LAB_WAIT;\n"
      "trap;\n"
      "LAB_DONE:\n"
      "}\n" ::"r"(a), "r"(parity), "r"(skip) : "memory");
}
__device__ __forceinline__ void mbar_wait_short(uint32_t a, uint32_t parity) {
  asm volatile("{\n.reg .pred p;\nLAB_WAIT:\nmbarrier.try_wait.parity.shared::cta.b64 p, [%0], %1;\n@!p bra.uni LAB_WAIT;\n}\n" ::"r"(a),
               "r"(parity) : "memory");
}
__device__ __forceinline__ bool mbar_test(uint32_t a, uint32_t parity) {
  uint32_t ok;
  asm volatile("{\n.reg .pred p;\nmbarrier.test_wait.parity.shared::cta.b64 p, [%1], %2;\nselp.u32 %0, 1, 0, p;\n}\n"
               : "=r"(ok) : "r"(a), "r"(parity) : "memory");
  return ok;
}
__device__ __forceinline__ void fence_async() { asm volatile("fence.proxy.async.shared::cta;" ::: "memory"); }
__device__ __forceinline__ void tma_box_warp(uint32_t dst, const CUtensorMap* tm, uint32_t bar, uint32_t bytes, int c, int x, int y) {
  asm volatile(
      "{\n.reg .pred p;\nelect.sync _|p, 0xffffffff;\n"
      "@p mbarrier.arrive.expect_tx.shared::cta.b64 _, [%2], %6;\n"
      "@p cp.async.bulk.tensor.3d.shared::cluster.global.mbarrier::complete_tx::bytes [%0], [%1, {%3, %4, %5}], [%2];\n}\n" ::"r"(dst),
      "l"(tm), "r"(bar), "r"(c), "r"(x), "r"(y), "r"(bytes) : "memory");
}
__device__ __forceinline__ void load_u_warp(uint32_t dst, const void* src, uint32_t bar) {
  asm volatile("{\n.reg .pred p;\nelect.sync _|p, 0xffffffff;\n"
               "@p mbarrier.arrive.expect_tx.shared::cta.b64 _, [%2], %3;\n"
               "@p cp.async.bulk.shared::cluster.global.mbarrier::complete_tx::bytes [%0], [%1], %3, [%2];\n}\n" ::"r"(dst),
               "l"(src), "r"(bar), "n"(USLAB) : "memory");
}
__device__ __forceinline__ uint2 lds64(uint32_t a) {
  uint2 v;
  asm volatile("ld.shared.v2.u32 {%0,%1}, [%2];" : "=r"(v.x), "=r"(v.y) : "r"(a) : "memory");
  return v;
}
__device__ __forceinline__ uint32_t lds32(uint32_t a) {
  uint32_t v;
  asm volatile("ld.shared.u32 %0, [%1];" : "=r"(v) : "r"(a) : "memory");
  return v;
}
__device__ __forceinline__ void store_v(uint32_t a, uint2 v, bool on) {
  v.x &= 0xFFFCFFFCu; v.y &= 0xFFFCFFFCu;
  if (on) asm volatile("st.shared.v2.u32 [%0], {%1,%2};" ::"r"(a), "r"(v.x), "r"(v.y) : "memory");
}
__device__ __forceinline__ void sched_barrier() { asm volatile("pmevent 0;" ::: "memory"); }
__device__ __forceinline__ void spin_cycles(uint32_t n) {
  asm volatile(
      "{\n.reg .pred p;\n.reg .u32 t0, t;\n"
      "mov.u32 t0, %%clock;\n"
      "LAB_SPIN:\n"
      "nanosleep.u32 50;\n"
      "mov.u32 t, %%clock;\nsub.u32 t, t, t0;\nsetp.lt.u32 p, t, %0;\n"
      "@p bra.uni LAB_SPIN;\n}\n" ::"r"(n) : "memory");
}
__device__ __forceinline__ void spin_until(uint32_t t0, uint32_t n) {
  asm volatile("{\n.reg .pred p;\n.reg .u32 t;\nLAB_SPIN:\nmov.u32 t, %%clock;\nsub.u32 t, t, %0;\nsetp.lt.u32 p, t, %1;\n@p bra.uni LAB_SPIN;\n}\n" ::"r"(t0),
               "r"(n) : "memory");
}
__device__ __forceinline__ uint32_t now() {
  uint32_t t;
  asm volatile("mov.u32 %0, %%clock;" : "=r"(t)::"memory");
  return t;
}
__device__ __forceinline__ uint32_t stage_enter(uint32_t* ctr, int lane) {
  uint32_t old;
  asm volatile("{\n.reg .pred p;\nsetp.eq.u32 p, %2, 0;\nld.relaxed.gpu.global.u32 %0, [%1];\n@p red.relaxed.gpu.global.add.u32 [%1], %3;\n}"
               : "=r"(old) : "l"(ctr), "r"(lane), "r"(lane + 1) : "memory");
  return old;
}
__device__ __forceinline__ void stage_wait(const uint32_t* ctr, uint32_t old) {
  asm volatile(
      "{\n.reg .pred p;\n.reg .u32 v, i;\n"
      "mov.u32 i, 0;\n"
      "LAB_POLL:\n"
      "ld.acquire.gpu.global.u32 v, [%0];\n"
      "xor.b32 v, v, %1;\nsetp.lt.s32 p, v, 0;\n"
      "@p bra.uni LAB_OUT;\n"
      "add.u32 i, i, 1;\nsetp.lt.u32 p, i, 4000000;\n"
      "@p bra.uni LAB_POLL;\n"
      "trap;\n"
      "LAB_OUT:\n"
      "fence.proxy.async.global;\n}\n" ::"l"(ctr), "r"(old) : "memory");
}
__device__ __forceinline__ void cluster_arrive_relaxed() { asm volatile("barrier.cluster.arrive.relaxed.aligned;" ::: "memory"); }
__device__ __forceinline__ void cluster_wait() { asm volatile("barrier.cluster.wait.acquire.aligned;" ::: "memory"); }

__host__ __device__ constexpr uint32_t h2const(float v) {
  double a = v < 0 ? -v : v;
  int e = 15;
  while (a >= 2) { a /= 2; e++; }
  while (a < 1) { a *= 2; e--; }
  const uint32_t h = (v < 0 ? 0x8000u : 0u) | ((e << 10) + (uint32_t)((a - 1) * 1024 + 0.5));
  return h | h << 16;
}
__device__ __forceinline__ uint32_t hfma2(uint32_t a, uint32_t b, uint32_t c) {
  uint32_t d;
  asm("fma.rn.f16x2 %0, %1, %2, %3;" : "=r"(d) : "r"(a), "r"(b), "r"(c));
  return d;
}
__device__ __forceinline__ uint32_t bmul2(uint32_t a, uint32_t b) {
  uint32_t d;
  asm("mul.rn.bf16x2 %0, %1, %2;" : "=r"(d) : "r"(a), "r"(b));
  return d;
}
__device__ __forceinline__ uint2 fma4(uint32_t k, const uint2& a, const uint2& c) { return make_uint2(hfma2(k, a.x, c.x), hfma2(k, a.y, c.y)); }
__device__ __forceinline__ uint32_t pack_bf16(float lo, float hi) {
  uint32_t d;
  asm("cvt.rn.bf16x2.f32 %0, %1, %2;" : "=r"(d) : "f"(hi), "f"(lo));
  return d;
}
__device__ __forceinline__ uint32_t pack_f16(float lo, float hi) {
  uint32_t d;
  asm("cvt.rn.f16x2.f32 %0, %1, %2;" : "=r"(d) : "f"(hi), "f"(lo));
  return d;
}

template <int AOFF, int BOFF>
__device__ __forceinline__ void wgmma192(uint32_t (&d)[48], uint64_t da, uint64_t db, uint32_t scale_d) {
  asm volatile(
      "{\n.reg .pred p;\n.reg .b64 qa, qb;\n"
      "setp.ne.b32 p, %50, 0;\n"
      "add.s64 qa, %48, %51;\nadd.s64 qb, %49, %52;\n"
      "wgmma.mma_async.sync.aligned.m64n192k16.f16.f16.f16 "
      "{%0, %1, %2, %3, %4, %5, %6, %7, %8, %9, %10, %11, %12, %13, %14, %15, "
      "%16, %17, %18, %19, %20, %21, %22, %23, %24, %25, %26, %27, %28, %29, %30, %31, "
      "%32, %33, %34, %35, %36, %37, %38, %39, %40, %41, %42, %43, %44, %45, %46, %47}, "
      "qa, qb, p, 1, 1, 0, 0;\n}\n"
      : "+r"(d[0]), "+r"(d[1]), "+r"(d[2]), "+r"(d[3]), "+r"(d[4]), "+r"(d[5]), "+r"(d[6]), "+r"(d[7]), "+r"(d[8]),
        "+r"(d[9]), "+r"(d[10]), "+r"(d[11]), "+r"(d[12]), "+r"(d[13]), "+r"(d[14]), "+r"(d[15]), "+r"(d[16]),
        "+r"(d[17]), "+r"(d[18]), "+r"(d[19]), "+r"(d[20]), "+r"(d[21]), "+r"(d[22]), "+r"(d[23]), "+r"(d[24]),
        "+r"(d[25]), "+r"(d[26]), "+r"(d[27]), "+r"(d[28]), "+r"(d[29]), "+r"(d[30]), "+r"(d[31]), "+r"(d[32]),
        "+r"(d[33]), "+r"(d[34]), "+r"(d[35]), "+r"(d[36]), "+r"(d[37]), "+r"(d[38]), "+r"(d[39]), "+r"(d[40]),
        "+r"(d[41]), "+r"(d[42]), "+r"(d[43]), "+r"(d[44]), "+r"(d[45]), "+r"(d[46]), "+r"(d[47])
      : "l"(da), "l"(db), "r"(scale_d), "n"(AOFF >> 4), "n"(BOFF >> 4));
}
__device__ __forceinline__ void wg_fence() { asm volatile("wgmma.fence.sync.aligned;" ::: "memory"); }
__device__ __forceinline__ void wg_commit() { asm volatile("wgmma.commit_group.sync.aligned;" ::: "memory"); }
template <int N>
__device__ __forceinline__ void wg_wait() { asm volatile("wgmma.wait_group.sync.aligned %0;" ::"n"(N) : "memory"); }
__device__ __forceinline__ void reg_fence(uint32_t (&d)[48]) {
#pragma unroll
  for (int i = 0; i < 48; i++) asm volatile("" : "+r"(d[i])::"memory");
}

constexpr uint32_t X_EXP = 17;
constexpr uint32_t X_LIM = ((15 + 8) << 7) - 1;
constexpr uint32_t U_LIM = ((15 + 6) << 10) - 1;
constexpr uint32_t Y_MIN = 0x3C00, Y_INF = 0x7C00;
constexpr uint32_t NAN2 = 0x7FFF7FFFu;
using Sample = uint4;
__device__ __forceinline__ uint4 ldg128(const uint4* p) {
  uint4 v;
  asm volatile("ld.global.v4.u32 {%0,%1,%2,%3}, [%4];" : "=r"(v.x), "=r"(v.y), "=r"(v.z), "=r"(v.w) : "l"(p));
  return v;
}
__device__ __forceinline__ Sample sample_w(const __nv_bfloat16* w, int lane) {
  const int q = lane >> 3;
  return ldg128((const uint4*)(w + ((q == 0 ? 1 : q == 1 ? 3 : 4) * CH + 47 * q) * CH + 64 * (q % 3)) + (lane & 7));
}
__device__ __forceinline__ Sample sample_x(const __nv_bfloat16* x, int r, int lane) {
  return ldg128((const uint4*)(x + (size_t)(((r >> 3) * 8 + 1 + lane % 6) * IMG + (r & 7) * 64 + 2 * lane) * CH) + lane % 24);
}
__device__ __forceinline__ uint32_t sample_exp(const Sample& s) {
  const uint32_t m = __vmaxu2(__vimax3_u16x2(s.x & NAN2, s.y & NAN2, s.z & NAN2), s.w & NAN2);
  return __reduce_max_sync(0xffffffffu, max(m & 0xFFFFu, m >> 16)) >> 7;
}

constexpr int NP = 16, NTASK = 24 * 36, NROUND = (NTASK + 8 * NP - 1) / (8 * NP);
__host__ __device__ constexpr int stage_end(int k) { return k == 0 ? 1 : k == 1 ? 3 : NROUND; }
__host__ __device__ constexpr int stage_first(int k) {
  for (int i = 0; i < NSTEP; i++) {
    const int h = step_p(i) / 3, n = step_n(i), g = n < 3 ? 3 * h + n : 2 * n + h;
    if ((g + 1) * 36 > stage_end(k - 1) * 8 * NP) return i;
  }
  return -1;
}
static_assert(stage_first(1) >= NU && stage_first(2) > stage_first(1), "stages");
struct Task {
  uint32_t n, s, kh, k;
  bool h;
  __device__ __forceinline__ Task(uint32_t t, int lane) {
    const uint32_t grp = t / 36, sub = t % 36;
    n = grp < 6 ? grp % 3 : grp >> 1;
    h = grp < 6 ? grp >= 3 : grp & 1;
    s = sub / 12, kh = (sub / 6) & 1, k = sub % 6 * 32 + lane;
  }
};
constexpr int WTASK = 24 * 64;
__device__ __forceinline__ void prep_load(uint32_t dst, const __nv_bfloat16* __restrict__ w, uint32_t t, int lane) {
  const Task q(min(t, NTASK - 1), 0);
  w += ((q.s * 24 + 2 * q.n + q.kh) * 8 + (lane >> 2)) * CH + q.k + (lane & 3) * 8;
#pragma unroll
  for (int r = 0; r < 3; r++)
    asm volatile("cp.async.cg.shared.global [%0], [%1], 16;" ::"r"(dst + r * 512 + lane * 16), "l"(w + r * 3 * CH * CH) : "memory");
}
__device__ __forceinline__ void prep_store(const float (&g)[3][8], uint4* u, uint32_t t, int lane) {
  const Task q(t, lane);
  const uint32_t n = q.n, s = q.s, kh = q.kh, k = q.k;
  const bool h = q.h;
  const uint32_t jn = (k >> 5) * 4 + ((k >> 1) & 3), row = ((k >> 3) & 3) * 2 + (k & 1);
  u += (((h ? 3 * NSUB : 0) + n) * USLAB + s * UTILE + jn * 256 + kh * 128 + row * 16) >> 4;
  constexpr float nA = -1.f / (2.f * A2 * DD), nB = 1.f / (2.f * B2 * DD);
  constexpr float f0 = nA / S1, f1 = nA / S2, f2 = nB / S3, f3 = nB / S4, f4 = 1.f / (A2 * B2);
  const float co[3][3] = {{h ? f3 : f0, h ? -PB * f3 : PA * f0, h ? B2 * f3 : A2 * f0},
                          {h ? f4 : f1, h ? 0.f : -PA * f1, h ? 0.f : A2 * f1},
                          {h ? 0.f : f2, h ? 0.f : PB * f2, h ? 1.f : B2 * f2}};
#pragma unroll
  for (int p = 0; p < 3; p++) {
    uint32_t o[4];
#pragma unroll
    for (int e = 0; e < 4; e++) {
      float v[2];
#pragma unroll
      for (int q = 0; q < 2; q++) v[q] = co[p][0] * g[0][2 * e + q] + co[p][1] * g[1][2 * e + q] + co[p][2] * g[2][2 * e + q];
      const uint32_t b = pack_bf16(v[0], v[1]);
      o[e] = pack_f16(__uint_as_float(b << 16), __uint_as_float(b & 0xFFFF0000u));
    }
    constexpr uint32_t lim = U_LIM * 0x10001u;
    if (__vimax3_u16x2(__vimax3_u16x2(lim, o[0] & NAN2, o[1] & NAN2), o[2] & NAN2, o[3] & NAN2) != lim) o[0] = NAN2;
    u[p * NSUB * USLAB / 16] = make_uint4(o[0], o[1], o[2], o[3]);
  }
}

constexpr int ROWB = IMG * CH * 2;

__device__ __forceinline__ int region_px(int r) { return (r >> 3) * 8 * IMG + (r & 7) * 64; }
__device__ __forceinline__ int halo_x(int r) { return (r & 7) * 64 - 1; }
__device__ __forceinline__ int halo_y(int r) { return (r >> 3) * 8 - 1; }

__device__ __noinline__ void direct_patch(const __nv_bfloat16* __restrict__ x, const __nv_bfloat16* __restrict__ w,
                                          __nv_bfloat16* __restrict__ out, int y0, int x0, int lane) {
  const int g = lane >> 2, t = lane & 3;
#pragma unroll 1
  for (int k0 = 0; k0 < CH; k0 += 48) {
    float acc[4][6][4] = {};
#pragma unroll 1
    for (int rs = 0; rs < 9; rs++) {
      const int iy = y0 + rs / 3 - 1, ix = x0 + rs % 3 - 1 + g;
#pragma unroll 2
      for (int c = 4 * t; c < CH; c += 16) {
        uint32_t b[6][2];
#pragma unroll
        for (int m = 0; m < 6; m++) {
          const uint32_t* p = (const uint32_t*)(w + (rs * CH + c + (m & 1) * 2) * CH + k0 + (m >> 1) * 16 + 2 * g);
          const uint32_t lo = p[0], hi = p[CH / 2];
          b[m & 6][m & 1] = __byte_perm(lo, hi, 0x5410);
          b[m | 1][m & 1] = __byte_perm(lo, hi, 0x7632);
        }
#pragma unroll
        for (int y = 0; y < 4; y++) {
          uint2 a[2];
#pragma unroll
          for (int h = 0; h < 2; h++)
            a[h] = (unsigned)(iy + y) < IMG && (unsigned)(ix + 8 * h) < IMG ? *(const uint2*)(x + ((iy + y) * IMG + ix + 8 * h) * CH + c)
                                                                           : make_uint2(0, 0);
#pragma unroll
          for (int m = 0; m < 6; m++)
            asm("mma.sync.aligned.m16n8k16.row.col.f32.bf16.bf16.f32 {%0,%1,%2,%3}, {%4,%5,%6,%7}, {%8,%9}, {%0,%1,%2,%3};"
                : "+f"(acc[y][m][0]), "+f"(acc[y][m][1]), "+f"(acc[y][m][2]), "+f"(acc[y][m][3])
                : "r"(a[0].x), "r"(a[1].x), "r"(a[0].y), "r"(a[1].y), "r"(b[m][0]), "r"(b[m][1]));
        }
      }
    }
#pragma unroll
    for (int y = 0; y < 4; y++)
#pragma unroll
      for (int m = 0; m < 6; m += 2)
#pragma unroll
        for (int h = 0; h < 2; h++)
          *(uint2*)(out + ((y0 + y) * IMG + x0 + g + 8 * h) * CH + k0 + m * 8 + 4 * t) =
              make_uint2(pack_bf16(acc[y][m][2 * h], acc[y][m + 1][2 * h]), pack_bf16(acc[y][m][2 * h + 1], acc[y][m + 1][2 * h + 1]));
  }
}

struct Descs { uint64_t a[2][6], b[NSTEP / NU + 1]; };
__host__ __device__ constexpr int slot_use(int i) {
  int c = 0;
  for (int j = 0; j < i; j++) c += vslot(step_p(j), step_n(j)) == vslot(step_p(i), step_n(i));
  return c;
}

__host__ __device__ constexpr int out_time(int q) {
  constexpr int t[24] = {
      49, 50, 51, 52, 54, 55, 56, 57, 59, 60, 61, 63, 64, 65, 66, 68, 69, 70, 72, 73, 75, 76, 78, 79};
  return t[q];
}
__host__ __device__ constexpr int out_at(int t) {
  for (int q = 0; q < 24; q++)
    if (out_time(q) % NSTEP == t) return q;
  return -1;
}
__host__ __device__ constexpr bool out_ok() {
  for (int q = 0; q < 24; q++)
    if (out_time(q) <= last_on(q / 6) || out_time(q) < PIV + (q < 12 ? 4 : 6) || out_time(q) >= first_on(q / 6) + NSTEP ||
        (q && out_time(q) <= out_time(q - 1)))
      return false;
  return true;
}
static_assert(out_ok(), "output plan");
constexpr int OUT_END = out_time(23) + 1 - NSTEP;

struct Consumer {
  uint32_t c1[48], c2[48], c3[48], c4[48];
  const uint64_t *descA, *descB;
  static constexpr uint32_t sb = SMEM_BASE;
  uint8_t* pout;
  int bid, nblk, nlong;
  uint32_t done;
  uint32_t osc, ymax, redo;
  bool lead, ok, odd;

  uint32_t one, zero;
  __device__ __forceinline__ bool always() {
    uint32_t v = one;
    asm volatile("" : "+r"(v));
    return v != 0;
  }
  __device__ __forceinline__ void axpy(uint32_t (&a)[48], uint32_t k, uint32_t (&b)[48]) {
    if (always()) {
      reg_fence(a); reg_fence(b);
#pragma unroll
      for (int i = 0; i < 48; i++) {
        a[i] = hfma2(k, b[i], a[i]);
        if (i % 12 == 11) {
          asm volatile("" : "+r"(a[i])::"memory");
          sched_barrier();
        }
      }
      reg_fence(a);
    }
  }
  uint32_t pa[4], pb[4], px[4];
  __device__ __forceinline__ uint32_t to_bf16(uint32_t h) {
    float lo, hi;
    asm("{\n.reg .b16 l, h;\n.reg .b32 m;\nmov.b32 {l, h}, %3;\ncvt.f32.f16 %0, l;\ncvt.f32.f16 %1, h;\n"
        "abs.f16x2 m, %3;\nmax.NaN.f16x2 %2, m, %2;\n}\n" : "=f"(lo), "=f"(hi), "+r"(ymax) : "r"(h));
    return bmul2(pack_bf16(lo, hi), osc);
  }
  template <int Q, int EXTRA>
  __device__ __forceinline__ void stg(const uint32_t (&v)[4], uint32_t on) {
    constexpr int y = Q < 6 ? 1 : Q < 12 ? 2 : Q < 18 ? 0 : 3;
    asm volatile("{\n.reg .pred p;\nsetp.ne.u32 p, %5, 0;\n@p st.global.cs.v4.u32 [%0+%6], {%1,%2,%3,%4};\n}\n" ::"l"(pout), "r"(v[0]),
                 "r"(v[1]), "r"(v[2]), "r"(v[3]), "r"(on), "n"(y * ROWB + (Q / 3) % 2 * 8 * (CH * 2) + Q % 3 * 128 + EXTRA) : "memory");
  }
  template <int Q, bool YIELD>
  __device__ __forceinline__ void convert(uint32_t (&a)[4], uint32_t (&b)[4], uint32_t (&send)[4]) {
    if constexpr (Q >= 0) {
      const uint32_t(&d)[48] = Q < 6 ? c1 : Q < 12 ? c2 : Q < 18 ? c3 : c4;
      constexpr int o = 16 * (Q % 3) + (Q / 3) % 2;
#pragma unroll
      for (int e = 0; e < 4; e++) {
        if (YIELD && e % 2 == 0) sched_barrier();
        a[e] = to_bf16(d[o + 2 * e]);
        b[e] = to_bf16(d[o + 8 + 2 * e]);
        send[e] = odd ? a[e] : b[e];
      }
    }
  }
  template <int QW, int QR, bool STEP>
  __device__ __forceinline__ void output(uint32_t on) {
    uint32_t u[4], v[4], a[4], b[4], send[4];
    if constexpr (!STEP) convert<QR, false>(a, b, send);
    sched_barrier();
#pragma unroll
    for (int e = 0; e < 4; e++) {
      u[e] = odd ? px[e] : pa[e];
      v[e] = odd ? pb[e] : px[e];
    }
    if constexpr (STEP) {
      convert<QR, true>(a, b, send);
      asm volatile("{\n.reg .pred p;\nsetp.ne.u32 p, %0, 0;\n@p pmevent 0;\n}" ::"r"((uint32_t)ok) : "memory");
      sched_barrier();
    }
    if constexpr (QW >= 0 && STEP) { stg<QW, 0>(u, on); stg<QW, CH * 2>(v, on); }
    if constexpr (QR >= 0) {
#pragma unroll
      for (int e = 0; e < 4; e++) px[e] = __shfl_xor_sync(0xffffffffu, send[e], 4), pa[e] = a[e], pb[e] = b[e];
    }
    if constexpr (QW >= 0 && !STEP) { stg<QW, 0>(u, on); stg<QW, CH * 2>(v, on); }
    sched_barrier();
  }
  __device__ __forceinline__ void range_check() {
    const uint32_t m = __reduce_max_sync(0xffffffffu, max(ymax & 0xFFFFu, ymax >> 16));
    redo |= (uint32_t)(m - Y_MIN >= Y_INF - Y_MIN) << done;
    ymax = 0;
  }
  template <int T, int Q0, int Q1, int Q = Q0>
  __device__ __forceinline__ void flush() {
    if constexpr (Q <= Q1) {
      constexpr int QW = Q > Q0 && out_time((Q + 23) % 24) >= T - 1 ? Q - 1 : -1, QR = Q < Q1 && out_time(Q % 24) >= T ? Q : -1;
      if constexpr (QW >= 0 || QR >= 0) output<QW, QR, false>(1);
      flush<T, Q0, Q1, Q + 1>();
    }
  }
  template <int I>
  __device__ __forceinline__ void hook() {
    constexpr float LP = PB * (PB - PA) / (2.f * A2), LM = PB * (PB + PA) / (2.f * A2);
    constexpr int QW = out_at((I + NSTEP - 1) % NSTEP), QR = out_at(I);
    if constexpr (QW >= 0 || QR >= 0) output<QW, QR, true>(I > OUT_END ? 1u : done);
    if constexpr (I == 20) {
      static_assert(OUT_END < 20, "pointer update");
      range_check();
      osc = lds32(sb + OFF_OSC);
      const int r = bid + done * nblk, d = region_px(r) - region_px(r - nblk);
      asm volatile("mad.wide.s32 %0, %1, 384, %0;" : "+l"(pout) : "r"(d));
    }
    if constexpr (I == 42) { if (bid >= nlong && done == 0) spin_cycles(29000); }
    if constexpr (I == PIV) axpy(c1, h2const(S3 * (B2 / A2) / S1), c3);
    if constexpr (I == PIV) axpy(c2, h2const(S3 * (B2 / A2) / S2), c3);
    if constexpr (I == PIV + 1) axpy(c4, h2const(-S3 / S4), c3);
    if constexpr (I == PIV + 1) axpy(c1, h2const(S4 * LP / S1), c4);
    if constexpr (I == PIV + 2) axpy(c2, h2const(S4 * LM / S2), c4);
    if constexpr (I == PIV + 2) axpy(c3, h2const(S4 * (-DD / A2)), c4);
    if constexpr (I == PIV + 3) { axpy(c1, h2const(-1.f / (2.f * PA)), c2); axpy(c2, h2const(PA), c1); }
    if constexpr (I == PIV + 4) axpy(c4, h2const(A2), c1);
    if constexpr (I == PIV + 5) axpy(c3, h2const(1.f / A2), c2);
  }

  template <int I, int END>
  __device__ __forceinline__ void steps() {
    if constexpr (I < END) {
      uint32_t(&d)[48] = step_acc(I) == 0 ? c1 : step_acc(I) == 1 ? c2 : step_acc(I) == 2 ? c3 : c4;
      constexpr int vo = vslot(step_p(I), step_n(I)) * VSLOT, uo = (I % NU) * USLAB;
      constexpr int J = (I + 1) % NSTEP;
      if (!ok) {
        mbar_wait_short(sb + BAR_UFULL + 8 * (I % NU), (I / NU) & 1);
        if constexpr (first_use(step_n(I)) == I) mbar_wait_short(sb + BAR_VFULL + 8 * (step_n(I) % NB), step_n(I) / NB);
      }
      const uint64_t da = descA[slot_use(I)], db = descB[I / NU];
      wg_fence();
      wgmma192<vo, uo>(d, da, db, first_on(step_acc(I)) == I ? 0u : 1u);
      wgmma192<vo + 16, uo + UTILE>(d, da, db, 1u);
      wgmma192<vo + 32, uo + 2 * UTILE>(d, da, db, 1u);
      wg_commit();
      ok = mbar_test(sb + BAR_UFULL + 8 * (J % NU), ((J / NU) & 1) ^ zero);
      if constexpr (first_use(step_n(J)) == J) ok &= mbar_test(sb + BAR_VFULL + 8 * (step_n(J) % NB), (step_n(J) / NB) ^ zero);
      hook<I>();
      wg_wait<0>();
      reg_fence(d);
      if (lead) mbar_arrive(sb + BAR_UEMPTY + 8 * (I % NU));
      if constexpr (gate_of(I) >= 0) { if (lead) mbar_arrive(sb + BAR_GATE + 8 * (gate_of(I) % NB)); }
      steps<I + 1, END>();
    }
  }
  template <int I>
  __device__ __forceinline__ void chain() {
    if constexpr (I < NSTEP) {
      static_assert(step_acc(I) == 3 && NSTEP - I <= NU, "chain");
      constexpr int vo = vslot(step_p(I), step_n(I)) * VSLOT, uo = (I % NU) * USLAB;
      mbar_wait_short(sb + BAR_UFULL + 8 * (I % NU), (I / NU) & 1);
      const uint64_t da = descA[5], db = descB[NSTEP / NU];
      wg_fence();
      wgmma192<vo, uo>(c4, da, db, 1u);
      wgmma192<vo + 16, uo + UTILE>(c4, da, db, 1u);
      wgmma192<vo + 32, uo + 2 * UTILE>(c4, da, db, 1u);
      wg_commit();
      chain<I + 1>();
    }
  }
  template <int T>
  __device__ __forceinline__ void finish(bool second) {
    if (second) {
      flush<T, 0, 18>();
      asm volatile("bar.sync 1, 256;" ::: "memory");
    }
    chain<T>();
    if (!second) {
      asm volatile("bar.arrive 1, 256;" ::: "memory");
      flush<T, 0, 18>();
    }
    wg_wait<0>();
    reg_fence(c4);
#pragma unroll
    for (int i = T; i < NSTEP; i++)
      if (lead) mbar_arrive(sb + BAR_UEMPTY + 8 * (i % NU));
    done++;
    flush<T, 18, 24>();
  }
};

struct SlotTab { uint32_t off[NSUB][8]; };
constexpr SlotTab make_slots() {
  SlotTab t = {};
  for (int n = 0; n < NSUB; n++)
    for (int p = 0; p < 6; p++) t.off[n][p] = vslot(p, n) * VSLOT;
  return t;
}
__constant__ __align__(64) SlotTab c_slots = make_slots();

constexpr int PF_X = 22, PF_Y = 2, PF_BYTES = PF_X * PF_Y * 16, U_LEAD = 10;
constexpr int PF_NB = 66 / PF_X * (10 / PF_Y);
static_assert(PF_BYTES + 16 <= OFF_U - OFF_SINK, "sink");
__host__ __device__ constexpr uint32_t pf_box(int k) {
  const int g = k / PF_NB, q = k % PF_NB;
  return 1u << 31 | (g / 3) << 30 | (g % 3) << 28 | (q / (10 / PF_Y) * PF_X) << 20 | (q % (10 / PF_Y) * PF_Y) << 16;
}
__host__ __device__ constexpr int slab_of(int i) { return step_p(i % NSTEP) * NSUB + step_n(i % NSTEP); }
struct LoadTab { uint32_t e[2 * NSTEP]; };
constexpr LoadTab make_loads() {
  LoadTab t = {};
  constexpr int win[6] = {19, 38, 42, 68, 69, 91};
  for (int k = 0, i = 0; k < 6 * PF_NB; k++) {
    const int g = k / PF_NB % 3, when = win[2 * g] + k % PF_NB * (win[2 * g + 1] - win[2 * g]) / PF_NB - (k < 3 * PF_NB ? NSTEP : 0);
    if (when >= 0 && when < NSTEP) t.e[NSTEP + when] = pf_box(k);
    if (k < PF_NB) continue;
    if (i < when) i = when;
    if (i < NSTEP) t.e[i++] = pf_box(k);
  }
  for (int i = 0; i < 2 * NSTEP; i++) t.e[i] |= slab_of(i + U_LEAD) << 8 | slab_of(i + NU);
  return t;
}
__constant__ __align__(64) LoadTab c_load = make_loads();

template <int BYTES>
__device__ __forceinline__ uint32_t warm(const void* p, uint32_t zero) {
  uint32_t v = ~0u;
#pragma unroll
  for (int o = 0; o < BYTES; o += 64) v &= ((const uint32_t*)p)[o / 4 + zero];
  return v;
}

__global__ void __launch_bounds__(384, 1) __cluster_dims__(1, 1, 1)
conv_kernel(const __grid_constant__ CUtensorMap tmX, const __grid_constant__ CUtensorMap tmH, const __grid_constant__ CUtensorMap tmP,
            const __nv_bfloat16* __restrict__ xin, const __nv_bfloat16* __restrict__ wgt, __nv_bfloat16* __restrict__ out,
            uint4* ubuf, uint32_t* arrived, int nblk, int nlong, int nmax, const __grid_constant__ Descs desc) {
  extern __shared__ uint8_t smem_raw[];
  const int tid = threadIdx.x, lane = tid & 31, bid = blockIdx.x;
  const int pidx = bid - (nblk - NP);
  constexpr uint32_t sb = SMEM_BASE;
  uint32_t epoch = 0;
  if (tid < 352) cluster_arrive_relaxed();
  if (tid < 256) {
    if (pidx >= 0) {
      uint32_t t = pidx * 8 + (tid >> 5);
      uint32_t stage = 0, wsm = sb + OFF_V + (tid >> 5) * NROUND * WTASK;
      prep_load(wsm, wgt, t, lane);
      const Sample ws = sample_w(wgt, lane);
      const float sw = __uint_as_float(max(253 - (int)sample_exp(ws), 0) << 23);
      const int klane = (lane & 6) * 4 + (lane >> 3) * 2 + (lane & 1);
#pragma unroll 1
      for (int round = 0; round < NROUND; round++, t += 8 * NP, wsm += WTASK) {
        asm volatile("cp.async.wait_all;" ::: "memory");
        __syncwarp();
        float g[3][8];
#pragma unroll
        for (int i = 0; i < 24; i++) {
          uint16_t v;
          asm volatile("ld.shared.u16 %0, [%1];" : "=h"(v) : "r"(wsm + i * 64 + klane * 2) : "memory");
          g[i / 8][i % 8] = __uint_as_float((uint32_t)v << 16) * sw;
        }
        if (t < NTASK) prep_store(g, ubuf, t, klane);
        if (round + 1 == stage_end(0) || round + 1 == stage_end(1) || round + 1 == NROUND) {
          asm volatile("bar.sync 1, 256;" ::: "memory");
          const uint32_t inc = pidx ? 1 : 0x80000001u - (stage ? NP : 2 * nblk);
          if (stage == 2) asm volatile("ld.relaxed.gpu.global.u32 %0, [%1];" : "=r"(epoch) : "l"(arrived + 64) : "memory");
          if (tid == 0) asm volatile("red.release.gpu.global.add.u32 [%0], %1;" ::"l"(arrived + 32 * stage), "r"(inc) : "memory");
          asm volatile("bar.sync 1, 256;" ::: "memory");
          if (stage++ == 0) {
#pragma unroll 1
            for (int k = 1; k < NROUND; k++) prep_load(wsm + k * WTASK, wgt, t + k * 8 * NP, lane);
          }
        }
      }
      if (tid < 32) asm volatile("bar.arrive 2, 64;" ::: "memory");
    } else if (tid < 32) {
      epoch = stage_enter(arrived, lane);
      spin_until(now(), 2200);
    }
  }
  if (tid >= 352) {
    asm volatile("prefetch.tensormap [%0];" ::"l"(&tmX) : "memory");
    constexpr uint64_t twos = ((1ull << NU) - 1) << (BAR_UEMPTY - OFF_BAR) / 8 | ((1ull << 2 * NB) - 1) << (BAR_VFULL - OFF_BAR) / 8;
    constexpr uint64_t threes = ((1ull << NB) - 1) << (BAR_VFULL - OFF_BAR) / 8;
    if (lane == 0) {
#pragma unroll
      for (int i = 0; i < NBAR; i++) mbar_init(sb + OFF_BAR + 8 * i, 1 + ((twos >> i) & 1) + ((threes >> i) & 1));
      asm volatile("fence.mbarrier_init.release.cluster;" ::: "memory");
      fence_async();
    }
    __syncwarp();
    cluster_arrive_relaxed();
    epoch = stage_enter(arrived, lane);
    if (pidx >= 0) asm volatile("bar.sync 2, 64;" ::: "memory");
    const uint32_t t0 = now();
#pragma unroll 1
    for (int k = 0, box = 0; k < 9; k++, box = box < 6 ? box + 3 : box - 5) {
      if (pidx < 0) spin_until(t0, k * 400);
      tma_box_warp(sb + OFF_X + box * XBOX, k < 8 ? &tmX : &tmH, sb + BAR_XFULL + 8 * box, k < 8 ? XBOX : XHBOX, 0, halo_x(bid) + k * 8,
                   halo_y(bid));
      if (k == 0) asm volatile("prefetch.tensormap [%0];\nprefetch.tensormap [%1];" ::"l"(&tmH), "l"(&tmP) : "memory");
    }
  }
  if (smem_u32(smem_raw) != SMEM_BASE) __trap();
  const int warp = __shfl_sync(0xffffffffu, tid >> 5, 0);

  if (warp < 8) {
    const int wg = warp >> 2;
    if (warp == 7) {
      spin_until(now(), 1300);
      if ((warm<sizeof(SlotTab)>(&c_slots, tid >> 10) & warm<sizeof(LoadTab)>(&c_load, tid >> 10)) == ~0u) __trap();
    }
    cluster_wait();
    if (warp == 0) {
      stage_wait(arrived, __shfl_sync(0xffffffffu, epoch, 0));
#pragma unroll
      for (int s = 0; s < NU; s++) load_u_warp(sb + OFF_U + s * USLAB, (const uint8_t*)ubuf + slab_of(s) * USLAB, sb + BAR_UFULL + 8 * s);
    }
    asm volatile("setmaxnreg.inc.sync.aligned.u32 224;");
    Consumer c;
#pragma unroll
    for (int i = 0; i < 48; i++) { c.c1[i] = 0; c.c2[i] = 0; c.c3[i] = 0; c.c4[i] = 0; }
#pragma unroll
    for (int e = 0; e < 4; e++) c.pa[e] = c.pb[e] = c.px[e] = 0;
    c.descA = desc.a[wg];
    c.descB = desc.b;
    c.lead = (tid & 127) == 0;
    c.one = __shfl_sync(0xffffffffu, nblk, 0);
    c.zero = __popc(__activemask()) >> 6;
    c.ok = false;
    c.bid = bid;
    c.nblk = nblk;
    c.nlong = nlong;
    c.odd = (lane >> 2) & 1;
    c.pout = (uint8_t*)out + (long long)(region_px(bid - nblk) + wg * 4 * IMG + (warp & 3) * 16 + (lane >> 3) * 2) * (CH * 2) + (lane & 7) * 16;
    c.done = c.osc = c.ymax = c.redo = 0;
    constexpr int ROT = 69;
    bool tail = false;
#pragma unroll 1
    do {
      wg_wait<0>();
      if (tail) {
        c.steps<ROT, NSTEP>();
        c.done++;
      }
      c.steps<0, ROT>();
      tail = c.always();
    } while (bid + (int)(c.done + 1) * nblk < NREG);
    c.finish<ROT>(wg);
    c.range_check();
    if (c.redo >> 1) {
      __syncwarp();
      for (int i = 0; i < (int)c.done; i++)
        if ((c.redo >> (i + 1)) & 1) {
          const int r = bid + i * nblk;
          direct_patch(xin, wgt, out, (r >> 3) * 8 + wg * 4, (r & 7) * 64 + (warp & 3) * 16, lane);
        }
    }
  } else {
    asm volatile("setmaxnreg.dec.sync.aligned.u32 56;");
    const int nitem = nmax - (bid >= nlong);
    if (warp == 11) {
      const uint8_t* ubase = (const uint8_t*)ubuf;
      epoch = __shfl_sync(0xffffffffu, epoch, 0);
      cluster_wait();
      const uint8_t* uline = ubase + (bid % 48 * 3 + lane) * 128;
      const bool ufetch = lane < 3 && bid < 96;
      int r = bid, npf = 0;
      uint32_t dst = sb + OFF_U, ebar = sb + BAR_UEMPTY, upar = 0;
      int i = 0, tab = 0;
#pragma unroll 1
      for (int left = nitem * NSTEP - NU; left > 0; left--) {
        const uint32_t e = c_load.e[tab + i];
        const uint8_t* src = ubase + (e & 255) * USLAB;
        const uint8_t* pu = uline + ((e >> 8) & 255) * USLAB;
        if (tab + i == stage_first(1) - NU) stage_wait(arrived + 32, epoch);
        if (tab + i == stage_first(2) - NU) stage_wait(arrived + 64, epoch);
        mbar_wait(ebar, upar);
        load_u_warp(dst, src, ebar - (BAR_UEMPTY - BAR_UFULL));
        const int rr = r + ((e >> 30) & 1) * nblk;
        if ((int)e < 0 && rr < NREG) {
          asm volatile("{\n.reg .pred p;\nelect.sync _|p, 0xffffffff;\n"
                       "@p cp.async.bulk.tensor.3d.shared::cluster.global.mbarrier::complete_tx::bytes [%0], [%1, {%3, %4, %5}], [%2];\n}\n"
                       ::"r"(sb + OFF_SINK), "l"(&tmP), "r"(sb + BAR_SINK), "r"((e >> 22) & 0xC0), "r"(halo_x(rr) + ((e >> 20) & 127)),
                       "r"(halo_y(rr) + ((e >> 16) & 15)) : "memory");
          npf++;
        }
        if (ufetch && tab + i >= NSTEP - U_LEAD && left > U_LEAD)
          asm volatile("cp.async.ca.shared.global.L2::128B [%0], [%1], 4;" ::"r"(sb + OFF_SINK + PF_BYTES + lane * 4), "l"(pu) : "memory");
        if (++i == NSTEP) { i = 0; r += nblk; tab = NSTEP; }
        const int s = i & (NU - 1);
        dst = sb + OFF_U + s * USLAB;
        ebar = sb + BAR_UEMPTY + 8 * s;
        if (s == 0) upar ^= 1;
      }
#pragma unroll 1
      for (int s = 0; s < NU; s++) mbar_wait(sb + BAR_UEMPTY + 8 * s, 1);
      if (lane == 0) asm volatile("mbarrier.arrive.expect_tx.shared::cta.b64 _, [%0], %1;" ::"r"(sb + BAR_SINK), "r"(npf * PF_BYTES) : "memory");
      mbar_wait(sb + BAR_SINK, 0);
      asm volatile("cp.async.wait_all;" ::: "memory");
    } else {
      const int w = warp - 8, col = (lane >> 1) & 7, chunk = lane >> 4;
      const uint32_t xbox = sb + OFF_X + w * 3 * XBOX, xbar = sb + BAR_XFULL + 24 * w;
      const uint32_t xl = xbox + col * 32 + ((chunk ^ (col >> 2)) << 4) + (lane & 1) * 8;
      const uint32_t vl = sb + OFF_V + chunk * VROW + w * 128 + (lane & 15) * 8;
      const bool in_row = w < 2 || col < 2;
      const uint32_t pitch2 = w < 2 ? 256 : 64, bytes2 = 10 * pitch2;
      const uint32_t xl2 = w < 2 ? xl + 2 * XBOX : xbox + 2 * XBOX + (col & 1) * 32 + chunk * 16 + (lane & 1) * 8;
      const CUtensorMap* tm2 = w < 2 ? &tmX : &tmH;
      auto xrow = [&](int j, int i) { return j < 2 ? xl + j * XBOX + i * 256 : xl2 + i * pitch2; };
      const Sample ws = sample_w(wgt, lane), xs = sample_x(xin, bid, lane);
      uint32_t xsc;
      {
        const int ex = sample_exp(xs), eo = ex + (int)sample_exp(ws) - (111 + X_EXP), es = 127 + X_EXP - ex;
        xsc = es >= 1 && eo >= 1 && eo <= 254 ? es * 0x00800080u : NAN2;
        asm volatile("st.shared.u32 [%0], %1;" ::"r"(sb + OFF_OSC), "r"(eo * 0x00800080u) : "memory");
      }
      constexpr uint32_t gate_par = [] { uint32_t m = 0; for (int n = 0; n < NSUB; n++) if ((n / NB) ^ (gate(n % NB) < 0)) m |= 1u << n; return m; }();
      constexpr uint32_t LIM2 = X_LIM * 0x10001u;
      cluster_wait();
      auto conv = [&](uint2& v, uint32_t m) {
        const uint32_t tx = bmul2(v.x, xsc), ty = bmul2(v.y, xsc), ux = tx & NAN2, uy = ty & NAN2;
        v = make_uint2(ux * 7 + tx, uy * 7 + ty);
        return __vimax3_u16x2(m, ux, uy);
      };
      uint32_t so[6] = {};
      auto planes = [&](const uint2* h, uint32_t m, uint32_t a, bool on) {
        constexpr uint32_t NB2 = h2const(-B2), NA2 = h2const(-A2);
        const uint2 e1 = fma4(NB2, h[2], h[4]), e2 = fma4(NA2, h[2], h[4]);
        store_v(a + so[4], fma4(NA2, fma4(NB2, h[0], h[2]), e1), on);
        const uint2 o1 = fma4(NB2, h[1], h[3]), o2 = fma4(NA2, h[1], h[3]);
        store_v(a + so[5], fma4(NA2, o1, fma4(NB2, h[3], h[5])), on);
        uint2 v = fma4(h2const(PA), o1, e1);
        if (m != LIM2) v.x = NAN2;
        store_v(a + so[0], v, on);
        store_v(a + so[1], fma4(h2const(-PA), o1, e1), on);
        store_v(a + so[2], fma4(h2const(PB), o2, e2), on);
        store_v(a + so[3], fma4(h2const(-PB), o2, e2), on);
      };
      int r = bid, n = 0;
      uint32_t par = 0;
#pragma unroll 1
      for (int left = nitem * NSUB; left > 0; left--) {
        const int nb = n >= NB ? n - NB : n;
        uint2 d[10];
        mbar_wait(xbar, par);
#pragma unroll
        for (int i = 0; i < 6; i++) d[i] = lds64(xrow(0, i));
#pragma unroll
        for (int p = 0; p < 6; p++) so[p] = c_slots.off[n][p];
        const uint32_t gpar = (gate_par >> n) & 1;
        if (++n == NSUB) { n = 0; r += nblk; }
        const int fc = n * 16, fx = halo_x(r) + w * 8, fy = halo_y(r);
#pragma unroll
        for (int j = 0; j < 3; j++) {
          const bool on = j < 2 || in_row;
#pragma unroll
          for (int i = 6; i < 10; i++) d[i] = lds64(xrow(j, i));
          const bool xok = j < 2 && mbar_test(xbar + 8 * (j + 1), par);
          sched_barrier();
          const uint32_t m45 = conv(d[5], conv(d[4], LIM2));
          const uint32_t ma = conv(d[3], conv(d[1], conv(d[0], conv(d[2], m45))));
          if (j == 0) mbar_wait(sb + BAR_GATE + 8 * nb, gpar);
          planes(d, ma, vl + j * 384, on);
          sched_barrier();
          const uint32_t mb = conv(d[9], conv(d[7], conv(d[6], conv(d[8], m45))));
          if (left > 1) tma_box_warp(xbox + j * XBOX, j < 2 ? &tmX : tm2, xbar + 8 * j, (j < 2 ? XBOX : bytes2) | (mb & 0x8000u), fc, fx + j * 24, fy);
          uint2 h[6];
#pragma unroll
          for (int i = 0; i < 6; i++) h[i] = d[4 + i];
          if (j < 2) {
            mbar_wait(xbar + 8 * (j + 1), par, xok);
#pragma unroll
            for (int i = 0; i < 6; i++) d[i] = lds64(xrow(j + 1, i));
          }
          sched_barrier();
          planes(h, mb, vl + j * 384 + VPIECE, on);
          sched_barrier();
        }
        fence_async();
        asm volatile("{\n.reg .pred p;\nelect.sync _|p, 0xffffffff;\n@p mbarrier.arrive.shared::cta.b64 _, [%0];\n}\n" ::"r"(sb + BAR_VFULL + 8 * nb) : "memory");
        par ^= 1;
      }
    }
  }
}

constexpr uint64_t make_desc(uint32_t off, uint32_t lbo, uint32_t sbo) {
  return (uint64_t)((SMEM_BASE + off) >> 4) | ((uint64_t)(lbo >> 4) << 16) | ((uint64_t)(sbo >> 4) << 32);
}

typedef CUresult (*EncodeFn)(CUtensorMap*, CUtensorMapDataType, cuuint32_t, void*, const cuuint64_t*, const cuuint64_t*,
                             const cuuint32_t*, const cuuint32_t*, CUtensorMapInterleave, CUtensorMapSwizzle,
                             CUtensorMapL2promotion, CUtensorMapFloatOOBfill);

}

extern "C" void kernel_launch(void* const* d_in, const int* in_sizes, int n_in, void* d_out, int out_size) {
  static EncodeFn enc = nullptr;
  static int nblk = 0;
  static uint4* ubuf;
  static uint32_t* arrived;
  if (!enc) {
    cudaGetSymbolAddress((void**)&ubuf, g_U);
    cudaGetSymbolAddress((void**)&arrived, g_arrived);
    cudaDriverEntryPointQueryResult qr;
    cudaGetDriverEntryPoint("cuTensorMapEncodeTiled", (void**)&enc, cudaEnableDefault, &qr);
    cudaFuncSetAttribute(conv_kernel, cudaFuncAttributeMaxDynamicSharedMemorySize, SMEM_BYTES);
    int dev;
    cudaGetDevice(&dev);
    cudaDeviceGetAttribute(&nblk, cudaDevAttrMultiProcessorCount, dev);
  }
  CUtensorMap tmX, tmH, tmP;
  const cuuint64_t dims[3] = {CH, IMG, IMG};
  const cuuint64_t strides[2] = {CH * 2, (cuuint64_t)CH * 2 * IMG};
  const cuuint32_t es[3] = {1, 1, 1};
  const cuuint32_t boxX[3] = {16, 8, 10}, boxH[3] = {16, 2, 10}, boxP[3] = {8, PF_X, PF_Y};
  enc(&tmH, CU_TENSOR_MAP_DATA_TYPE_BFLOAT16, 3, d_in[0], dims, strides, boxH, es, CU_TENSOR_MAP_INTERLEAVE_NONE,
      CU_TENSOR_MAP_SWIZZLE_NONE, CU_TENSOR_MAP_L2_PROMOTION_L2_64B, CU_TENSOR_MAP_FLOAT_OOB_FILL_NONE);
  enc(&tmP, CU_TENSOR_MAP_DATA_TYPE_BFLOAT16, 3, d_in[0], dims, strides, boxP, es, CU_TENSOR_MAP_INTERLEAVE_NONE,
      CU_TENSOR_MAP_SWIZZLE_NONE, CU_TENSOR_MAP_L2_PROMOTION_L2_128B, CU_TENSOR_MAP_FLOAT_OOB_FILL_NONE);
  enc(&tmX, CU_TENSOR_MAP_DATA_TYPE_BFLOAT16, 3, d_in[0], dims, strides, boxX, es, CU_TENSOR_MAP_INTERLEAVE_NONE,
      CU_TENSOR_MAP_SWIZZLE_32B, CU_TENSOR_MAP_L2_PROMOTION_L2_64B, CU_TENSOR_MAP_FLOAT_OOB_FILL_NONE);
  Descs desc = {};
  for (int i = 0; i < 6; i++) { desc.a[0][i] = make_desc(OFF_V, VROW, 128); desc.a[1][i] = make_desc(OFF_V + VPIECE, VROW, 128); }
  for (int i = 0; i <= NSTEP / NU; i++) desc.b[i] = make_desc(OFF_U, 128, 256);
  conv_kernel<<<nblk, 384, SMEM_BYTES>>>(tmX, tmH, tmP, (const __nv_bfloat16*)d_in[0], (const __nv_bfloat16*)d_in[1], (__nv_bfloat16*)d_out, ubuf, arrived, nblk,
                                         NREG % nblk ? NREG % nblk : nblk, (NREG + nblk - 1) / nblk, desc);
}
```

```cpp
#include <cuda_runtime.h>
#include <cuda_bf16.h>
#include <cuda.h>
#include <stdint.h>

namespace {

constexpr int IMG = 512, CH = 192;
constexpr float PA = 0.6875f, PB = 1.5f;
constexpr float A2 = PA * PA, B2 = PB * PB, DD = B2 - A2;

constexpr int NSTEP = 72, NSUB = 12;
__host__ __device__ constexpr int sched(int i) {
  constexpr int t[NSTEP] = {
      0x00, 0x10, 0x20, 0x01, 0x11, 0x21, 0x02, 0x12, 0x22, 0x30, 0x31, 0x32, 0x23, 0x33, 0x03, 0x13, 0x24, 0x34,
      0x04, 0x14, 0x25, 0x35, 0x05, 0x15, 0x26, 0x36, 0x06, 0x16, 0x27, 0x37, 0x07, 0x17, 0x28, 0x38, 0x08, 0x18,
      0x29, 0x39, 0x09, 0x19, 0x2a, 0x3a, 0x0a, 0x1a, 0x2b, 0x3b, 0x1b, 0x0b, 0x40, 0x4b, 0x50, 0x41, 0x51, 0x4a,
      0x49, 0x48, 0x47, 0x42, 0x52, 0x46, 0x45, 0x5b, 0x44, 0x43, 0x5a, 0x53, 0x59, 0x58, 0x57, 0x56, 0x54, 0x55};
  return t[i];
}
__host__ __device__ constexpr int step_p(int i) { return sched(i) >> 4; }
__host__ __device__ constexpr int step_n(int i) { return sched(i) & 15; }
__host__ __device__ constexpr int step_acc(int i) { return step_p(i) < 4 ? step_p(i) : step_p(i) - 2; }
__host__ __device__ constexpr int first_on(int acc) {
  for (int i = 0; i < NSTEP; i++)
    if (step_acc(i) == acc) return i;
  return -1;
}
__host__ __device__ constexpr int last_on(int acc) {
  for (int i = NSTEP - 1; i >= 0; i--)
    if (step_acc(i) == acc) return i;
  return -1;
}
__host__ __device__ constexpr int find_step(int p, int n) {
  for (int i = 0; i < NSTEP; i++)
    if (sched(i) == p * 16 + n) return i;
  return -1;
}
__host__ __device__ constexpr int first_use(int n) {
  for (int i = 0; i < NSTEP; i++)
    if (step_n(i) == n) return i;
  return -1;
}
constexpr float S1 = 1.f / PA, S2 = 1.f / (2.f * A2), S3 = -A2 / (2.f * DD), S4 = -1.f / (PB * DD);
constexpr int PIV = find_step(3, NSUB - 1);
static_assert(find_step(2, NSUB - 1) == PIV - 1 && last_on(1) == PIV + 1 && last_on(0) == PIV + 2 && PIV + 3 == 4 * NSUB &&
              step_p(PIV + 3) == 4 && step_p(PIV + 4) == 4 && step_p(PIV + 5) == 5, "basis change");

constexpr int NV = 32, NB = 6;
__host__ __device__ constexpr int vslot(int p, int n) {
  constexpr int t[6][NSUB] = {
      {26, 21, 15, 20, 17, 26, 28, 23, 24, 30, 4, 28}, {30, 23, 25, 22, 30, 24, 25, 0, 26, 27, 1, 27}, {28, 17, 14,
      18, 28, 19, 20, 21, 1, 25, 0, 30}, {27, 19, 24, 16, 23, 27, 22, 30, 3, 28, 2, 3}, {7, 6, 8, 10, 12, 14, 15,
      17, 19, 21, 23, 26}, {31, 29, 9, 11, 13, 5, 16, 18, 20, 22, 24, 25}};
  return t[p][n];
}
__host__ __device__ constexpr int gate(int n) {
  constexpr int t[NSUB] = {-20, -14, -8, -2, 5, 11, 16, 21, 25, 29, 34, 39};
  return t[n];
}
__host__ __device__ constexpr int gate_of(int i) {
  for (int n = 0; n < NSUB; n++)
    if ((gate(n) + NSTEP) % NSTEP == i) return n;
  return -1;
}
__host__ __device__ constexpr bool gates_ok() {
  for (int n = 0; n < NSUB; n++) {
    for (int p = 0; p < 6; p++)
      for (int d = 1; d <= NSUB; d++)
        for (int q = 0; q < 6; q++) {
          const int m = (n - d + NSUB) % NSUB;
          if (vslot(q, m) == vslot(p, n) && (find_step(q, m) - (n - d < 0 ? NSTEP : 0) > gate(n) || (m == n && p != q))) return false;
        }
    if (n > 0 && (gate(n) <= gate(n - 1) || first_use(n) <= first_use(n - 1))) return false;
    if (gate(n) >= first_use(n)) return false;
    if (gate((n + NB) % NSUB) + (n >= NB ? NSTEP : 0) < first_use(n)) return false;
  }
  return gate(0) + NSTEP > gate(NSUB - 1) && gate(NB) >= 0;
}
static_assert(gates_ok(), "gates");

constexpr int UTILE = CH * 16 * 2;
constexpr int USLAB = 3 * UTILE;
constexpr int NU = 4;
constexpr int VROW = 66 * 16;
constexpr int VPIECE = 2 * VROW;
constexpr int VSLOT = 2 * VPIECE;
constexpr int XBOX = 10 * 8 * 32;
constexpr int XHBOX = 10 * 2 * 32;
constexpr int UX_FIRST = 52, UX_COUNT = 8, UX_GATE = UX_FIRST - NU - 1;
__host__ __device__ constexpr bool uextra(int i) {
  const int d = (i - UX_FIRST + NSTEP) % NSTEP;
  return d % (NU + 1) == 0 && d / (NU + 1) < UX_COUNT;
}
__host__ __device__ constexpr int uindex(int i) {
  int c = 0;
  for (int j = 0; j < i; j++) c += uextra(j) == uextra(i);
  return c;
}
__host__ __device__ constexpr int uslot(int i) { return uextra(i) ? NU : uindex(i) % NU; }
__host__ __device__ constexpr int uuse(int i) { return uextra(i) ? uindex(i) : uindex(i) / NU; }
__host__ __device__ constexpr int utrigger(int j) {
  if (j == UX_FIRST) return UX_GATE;
  int i = j - 1;
  while (uslot((i + NSTEP) % NSTEP) != uslot(j)) i--;
  return i;
}
template <int I> constexpr int USLOT = uslot(I);
template <int I> constexpr int UUSE = uuse(I);
__host__ __device__ constexpr bool uring_ok() {
  for (int n = 0; n < NSUB; n++)
    for (int p = 0; p < 6; p++)
      if (vslot(p, n) * VSLOT < USLAB &&
          (find_step(p, n) > UX_GATE || gate(n) < UX_FIRST + (NU + 1) * (UX_COUNT - 1) - NSTEP))
        return false;
  return UX_COUNT % 2 == 0 && (NSTEP - UX_COUNT) % (2 * NU) == 0;
}
static_assert(uring_ok(), "U ring");

constexpr int OFF_X = 0;
constexpr int OFF_SINK = OFF_X + 8 * XBOX + XHBOX;
constexpr int OFF_U = OFF_SINK + 768;
constexpr int OFF_V = OFF_U + NU * USLAB;
constexpr int OFF_BAR = OFF_V + NV * VSLOT;
constexpr int BAR_UFULL = OFF_BAR;
constexpr int BAR_UEMPTY = BAR_UFULL + 8 * (NU + 1);
constexpr int BAR_XFULL = BAR_UEMPTY + 8 * (NU + 1);
constexpr int BAR_VFULL = BAR_XFULL + 8 * 9;
constexpr int BAR_GATE = BAR_VFULL + 8 * NB;
constexpr int BAR_SINK = BAR_GATE + 8 * NB;
constexpr int OFF_OSC = BAR_SINK + 8;
constexpr int NBAR = (OFF_OSC - OFF_BAR) / 8;
constexpr int SMEM_BYTES = OFF_OSC + 8;
constexpr uint32_t SMEM_BASE = 1024;
static_assert(SMEM_BYTES <= 232448, "smem");

constexpr int NREG = 512;

__device__ __align__(128) uint4 g_U[NSTEP * USLAB / 16];
__device__ uint32_t g_arrived[3 * 32];

__device__ __forceinline__ uint32_t smem_u32(const void* p) { return (uint32_t)__cvta_generic_to_shared(p); }
__device__ __forceinline__ void mbar_init(uint32_t a, int c) {
  asm volatile("mbarrier.init.shared::cta.b64 [%0], %1;" ::"r"(a), "r"(c) : "memory");
}
__device__ __forceinline__ void mbar_arrive(uint32_t a) {
  asm volatile("mbarrier.arrive.shared::cta.b64 _, [%0];" ::"r"(a) : "memory");
}
__device__ __forceinline__ void mbar_wait(uint32_t a, uint32_t parity, uint32_t skip = 0) {
  asm volatile(
      "{\n"
      ".reg .pred p;\n"
      ".reg .u32 n;\n"
      "setp.ne.u32 p, %2, 0;\n"
      "@p bra.uni LAB_DONE;\n"
      "mov.u32 n, 0;\n"
      "LAB_WAIT:\n"
      "mbarrier.try_wait.parity.shared::cta.b64 p, [%0], %1;\n"
      "@p bra.uni LAB_DONE;\n"
      "add.u32 n, n, 1;\n"
      "setp.lt.u32 p, n, 4000000;\n"
      "@p bra.uni LAB_WAIT;\n"
      "trap;\n"
      "LAB_DONE:\n"
      "}\n" ::"r"(a), "r"(parity), "r"(skip) : "memory");
}
__device__ __forceinline__ void mbar_wait_short(uint32_t a, uint32_t parity) {
  asm volatile("{\n.reg .pred p;\nLAB_WAIT:\nmbarrier.try_wait.parity.shared::cta.b64 p, [%0], %1;\n@!p bra.uni LAB_WAIT;\n}\n" ::"r"(a),
               "r"(parity) : "memory");
}
__device__ __forceinline__ bool mbar_test(uint32_t a, uint32_t parity) {
  uint32_t ok;
  asm volatile("{\n.reg .pred p;\nmbarrier.test_wait.parity.shared::cta.b64 p, [%1], %2;\nselp.u32 %0, 1, 0, p;\n}\n"
               : "=r"(ok) : "r"(a), "r"(parity) : "memory");
  return ok;
}
__device__ __forceinline__ void fence_async() { asm volatile("fence.proxy.async.shared::cta;" ::: "memory"); }
__device__ __forceinline__ void tma_box_warp(uint32_t dst, const CUtensorMap* tm, uint32_t bar, uint32_t bytes, int c, int x, int y) {
  asm volatile(
      "{\n.reg .pred p;\nelect.sync _|p, 0xffffffff;\n"
      "@p mbarrier.arrive.expect_tx.shared::cta.b64 _, [%2], %6;\n"
      "@p cp.async.bulk.tensor.3d.shared::cluster.global.mbarrier::complete_tx::bytes [%0], [%1, {%3, %4, %5}], [%2];\n}\n" ::"r"(dst),
      "l"(tm), "r"(bar), "r"(c), "r"(x), "r"(y), "r"(bytes) : "memory");
}
__device__ __forceinline__ void load_u_warp(uint32_t dst, const void* src, uint32_t bar) {
  asm volatile("{\n.reg .pred p;\nelect.sync _|p, 0xffffffff;\n"
               "@p mbarrier.arrive.expect_tx.shared::cta.b64 _, [%2], %3;\n"
               "@p cp.async.bulk.shared::cluster.global.mbarrier::complete_tx::bytes [%0], [%1], %3, [%2];\n}\n" ::"r"(dst),
               "l"(src), "r"(bar), "n"(USLAB) : "memory");
}
__device__ __forceinline__ void refill_u(uint32_t ebar, uint32_t parity, uint32_t on, uint32_t dst, const void* src) {
  asm volatile(
      "{\n.reg .pred p;\n.reg .u32 n;\n"
      "mov.u32 n, 0;\n"
      "LAB_WAIT:\n"
      "mbarrier.try_wait.parity.shared::cta.b64 p, [%0], %1;\n"
      "@p bra.uni LAB_DONE;\n"
      "add.u32 n, n, 1;\nsetp.lt.u32 p, n, 4000000;\n"
      "@p bra.uni LAB_WAIT;\n"
      "trap;\n"
      "LAB_DONE:\n"
      "setp.eq.u32 p, %2, 0;\n"
      "@p bra.uni LAB_OUT;\n"
      "elect.sync _|p, 0xffffffff;\n"
      "@p mbarrier.arrive.expect_tx.shared::cta.b64 _, [%5], %6;\n"
      "@p cp.async.bulk.shared::cluster.global.mbarrier::complete_tx::bytes [%3], [%4], %6, [%5];\n"
      "LAB_OUT:\n}\n" ::"r"(ebar), "r"(parity), "r"(on), "r"(dst), "l"(src), "r"(ebar - (BAR_UEMPTY - BAR_UFULL)), "n"(USLAB) : "memory");
}
__device__ __forceinline__ uint2 lds64(uint32_t a) {
  uint2 v;
  asm volatile("ld.shared.v2.u32 {%0,%1}, [%2];" : "=r"(v.x), "=r"(v.y) : "r"(a) : "memory");
  return v;
}
__device__ __forceinline__ uint32_t lds32(uint32_t a) {
  uint32_t v;
  asm volatile("ld.shared.u32 %0, [%1];" : "=r"(v) : "r"(a) : "memory");
  return v;
}
__device__ __forceinline__ void store_v(uint32_t a, uint2 v, bool on) {
  v.x &= 0xFFFCFFFCu; v.y &= 0xFFFCFFFCu;
  if (on) asm volatile("st.shared.v2.u32 [%0], {%1,%2};" ::"r"(a), "r"(v.x), "r"(v.y) : "memory");
}
__device__ __forceinline__ void sched_barrier() { asm volatile("pmevent 0;" ::: "memory"); }
__device__ __forceinline__ void spin_cycles(uint32_t n) {
  asm volatile(
      "{\n.reg .pred p;\n.reg .u32 t0, t;\n"
      "mov.u32 t0, %%clock;\n"
      "LAB_SPIN:\n"
      "nanosleep.u32 50;\n"
      "mov.u32 t, %%clock;\nsub.u32 t, t, t0;\nsetp.lt.u32 p, t, %0;\n"
      "@p bra.uni LAB_SPIN;\n}\n" ::"r"(n) : "memory");
}
__device__ __forceinline__ void spin_until(uint32_t t0, uint32_t n) {
  asm volatile("{\n.reg .pred p;\n.reg .u32 t;\nLAB_SPIN:\nmov.u32 t, %%clock;\nsub.u32 t, t, %0;\nsetp.lt.u32 p, t, %1;\n@p bra.uni LAB_SPIN;\n}\n" ::"r"(t0),
               "r"(n) : "memory");
}
__device__ __forceinline__ uint32_t now() {
  uint32_t t;
  asm volatile("mov.u32 %0, %%clock;" : "=r"(t)::"memory");
  return t;
}
__device__ __forceinline__ uint32_t stage_enter(uint32_t* ctr, int lane) {
  uint32_t old;
  asm volatile("{\n.reg .pred p;\nsetp.eq.u32 p, %2, 0;\nld.relaxed.gpu.global.u32 %0, [%1];\n@p red.relaxed.gpu.global.add.u32 [%1], %3;\n}"
               : "=r"(old) : "l"(ctr), "r"(lane), "r"(lane + 1) : "memory");
  return old;
}
__device__ __forceinline__ void stage_wait(const uint32_t* ctr, uint32_t old) {
  asm volatile(
      "{\n.reg .pred p;\n.reg .u32 v, i;\n"
      "mov.u32 i, 0;\n"
      "LAB_POLL:\n"
      "ld.acquire.gpu.global.u32 v, [%0];\n"
      "xor.b32 v, v, %1;\nsetp.lt.s32 p, v, 0;\n"
      "@p bra.uni LAB_OUT;\n"
      "add.u32 i, i, 1;\nsetp.lt.u32 p, i, 4000000;\n"
      "@p bra.uni LAB_POLL;\n"
      "trap;\n"
      "LAB_OUT:\n"
      "fence.proxy.async.global;\n}\n" ::"l"(ctr), "r"(old) : "memory");
}
__device__ __forceinline__ void cluster_arrive_relaxed() { asm volatile("barrier.cluster.arrive.relaxed.aligned;" ::: "memory"); }
__device__ __forceinline__ void cluster_wait() { asm volatile("barrier.cluster.wait.acquire.aligned;" ::: "memory"); }

__host__ __device__ constexpr uint32_t h2const(float v) {
  double a = v < 0 ? -v : v;
  int e = 15;
  while (a >= 2) { a /= 2; e++; }
  while (a < 1) { a *= 2; e--; }
  const uint32_t h = (v < 0 ? 0x8000u : 0u) | ((e << 10) + (uint32_t)((a - 1) * 1024 + 0.5));
  return h | h << 16;
}
__device__ __forceinline__ uint32_t hfma2(uint32_t a, uint32_t b, uint32_t c) {
  uint32_t d;
  asm("fma.rn.f16x2 %0, %1, %2, %3;" : "=r"(d) : "r"(a), "r"(b), "r"(c));
  return d;
}
__device__ __forceinline__ uint32_t bmul2(uint32_t a, uint32_t b) {
  uint32_t d;
  asm("mul.rn.bf16x2 %0, %1, %2;" : "=r"(d) : "r"(a), "r"(b));
  return d;
}
__device__ __forceinline__ uint2 fma4(uint32_t k, const uint2& a, const uint2& c) { return make_uint2(hfma2(k, a.x, c.x), hfma2(k, a.y, c.y)); }
__device__ __forceinline__ uint32_t pack_bf16(float lo, float hi) {
  uint32_t d;
  asm("cvt.rn.bf16x2.f32 %0, %1, %2;" : "=r"(d) : "f"(hi), "f"(lo));
  return d;
}
__device__ __forceinline__ uint32_t pack_f16(float lo, float hi) {
  uint32_t d;
  asm("cvt.rn.f16x2.f32 %0, %1, %2;" : "=r"(d) : "f"(hi), "f"(lo));
  return d;
}

template <int AOFF, int BOFF>
__device__ __forceinline__ void wgmma192(uint32_t (&d)[48], uint64_t da, uint64_t db, uint32_t scale_d) {
  asm volatile(
      "{\n.reg .pred p;\n.reg .b64 qa, qb;\n"
      "setp.ne.b32 p, %50, 0;\n"
      "add.s64 qa, %48, %51;\nadd.s64 qb, %49, %52;\n"
      "wgmma.mma_async.sync.aligned.m64n192k16.f16.f16.f16 "
      "{%0, %1, %2, %3, %4, %5, %6, %7, %8, %9, %10, %11, %12, %13, %14, %15, "
      "%16, %17, %18, %19, %20, %21, %22, %23, %24, %25, %26, %27, %28, %29, %30, %31, "
      "%32, %33, %34, %35, %36, %37, %38, %39, %40, %41, %42, %43, %44, %45, %46, %47}, "
      "qa, qb, p, 1, 1, 0, 0;\n}\n"
      : "+r"(d[0]), "+r"(d[1]), "+r"(d[2]), "+r"(d[3]), "+r"(d[4]), "+r"(d[5]), "+r"(d[6]), "+r"(d[7]), "+r"(d[8]),
        "+r"(d[9]), "+r"(d[10]), "+r"(d[11]), "+r"(d[12]), "+r"(d[13]), "+r"(d[14]), "+r"(d[15]), "+r"(d[16]),
        "+r"(d[17]), "+r"(d[18]), "+r"(d[19]), "+r"(d[20]), "+r"(d[21]), "+r"(d[22]), "+r"(d[23]), "+r"(d[24]),
        "+r"(d[25]), "+r"(d[26]), "+r"(d[27]), "+r"(d[28]), "+r"(d[29]), "+r"(d[30]), "+r"(d[31]), "+r"(d[32]),
        "+r"(d[33]), "+r"(d[34]), "+r"(d[35]), "+r"(d[36]), "+r"(d[37]), "+r"(d[38]), "+r"(d[39]), "+r"(d[40]),
        "+r"(d[41]), "+r"(d[42]), "+r"(d[43]), "+r"(d[44]), "+r"(d[45]), "+r"(d[46]), "+r"(d[47])
      : "l"(da), "l"(db), "r"(scale_d), "n"(AOFF >> 4), "n"(BOFF >> 4));
}
__device__ __forceinline__ void wg_fence() { asm volatile("wgmma.fence.sync.aligned;" ::: "memory"); }
__device__ __forceinline__ void wg_commit() { asm volatile("wgmma.commit_group.sync.aligned;" ::: "memory"); }
template <int N>
__device__ __forceinline__ void wg_wait() { asm volatile("wgmma.wait_group.sync.aligned %0;" ::"n"(N) : "memory"); }
__device__ __forceinline__ void reg_fence(uint32_t (&d)[48]) {
#pragma unroll
  for (int i = 0; i < 48; i++) asm volatile("" : "+r"(d[i])::"memory");
}

constexpr uint32_t X_EXP = 17;
constexpr uint32_t X_LIM = ((15 + 8) << 7) - 1;
constexpr uint32_t U_LIM = ((15 + 6) << 10) - 1;
constexpr uint32_t Y_MIN = 0x3C00, Y_INF = 0x7C00;
constexpr uint32_t NAN2 = 0x7FFF7FFFu;
using Sample = uint4;
__device__ __forceinline__ uint4 ldg128(const uint4* p) {
  uint4 v;
  asm volatile("ld.global.v4.u32 {%0,%1,%2,%3}, [%4];" : "=r"(v.x), "=r"(v.y), "=r"(v.z), "=r"(v.w) : "l"(p));
  return v;
}
__device__ __forceinline__ Sample sample_w(const __nv_bfloat16* w, int lane) {
  const int q = lane >> 3;
  return ldg128((const uint4*)(w + ((q == 0 ? 1 : q == 1 ? 3 : 4) * CH + 47 * q) * CH + 64 * (q % 3)) + (lane & 7));
}
__device__ __forceinline__ Sample sample_x(const __nv_bfloat16* x, int r, int lane) {
  return ldg128((const uint4*)(x + (size_t)(((r >> 3) * 8 + 1 + lane % 6) * IMG + (r & 7) * 64 + 2 * lane) * CH) + lane % 24);
}
__device__ __forceinline__ uint32_t sample_exp(const Sample& s) {
  const uint32_t m = __vmaxu2(__vimax3_u16x2(s.x & NAN2, s.y & NAN2, s.z & NAN2), s.w & NAN2);
  return __reduce_max_sync(0xffffffffu, max(m & 0xFFFFu, m >> 16)) >> 7;
}

constexpr int NP = 16, NTASK = 24 * 36, NROUND = (NTASK + 8 * NP - 1) / (8 * NP);
__host__ __device__ constexpr int stage_end(int k) { return k == 0 ? 1 : k == 1 ? 3 : NROUND; }
__host__ __device__ constexpr int stage_first(int k) {
  for (int i = 0; i < NSTEP; i++) {
    const int h = step_p(i) / 3, n = step_n(i), g = n < 3 ? 3 * h + n : 2 * n + h;
    if ((g + 1) * 36 > stage_end(k - 1) * 8 * NP) return i;
  }
  return -1;
}
static_assert(utrigger(stage_first(1)) >= 0 && stage_first(2) > stage_first(1), "stages");
struct Task {
  uint32_t n, s, kh, k;
  bool h;
  __device__ __forceinline__ Task(uint32_t t, int lane) {
    const uint32_t grp = t / 36, sub = t % 36;
    n = grp < 6 ? grp % 3 : grp >> 1;
    h = grp < 6 ? grp >= 3 : grp & 1;
    s = sub / 12, kh = (sub / 6) & 1, k = sub % 6 * 32 + lane;
  }
};
constexpr int WTASK = 24 * 64;
__device__ __forceinline__ void prep_load(uint32_t dst, const __nv_bfloat16* __restrict__ w, uint32_t t, int lane) {
  const Task q(min(t, NTASK - 1), 0);
  w += ((q.s * 24 + 2 * q.n + q.kh) * 8 + (lane >> 2)) * CH + q.k + (lane & 3) * 8;
#pragma unroll
  for (int r = 0; r < 3; r++)
    asm volatile("cp.async.cg.shared.global [%0], [%1], 16;" ::"r"(dst + r * 512 + lane * 16), "l"(w + r * 3 * CH * CH) : "memory");
}
__device__ __forceinline__ void prep_store(const float (&g)[3][8], uint4* u, uint32_t t, int lane) {
  const Task q(t, lane);
  const uint32_t n = q.n, s = q.s, kh = q.kh, k = q.k;
  const bool h = q.h;
  const uint32_t jn = (k >> 5) * 4 + ((k >> 1) & 3), row = ((k >> 3) & 3) * 2 + (k & 1);
  u += (((h ? 3 * NSUB : 0) + n) * USLAB + s * UTILE + jn * 256 + kh * 128 + row * 16) >> 4;
  constexpr float nA = -1.f / (2.f * A2 * DD), nB = 1.f / (2.f * B2 * DD);
  constexpr float f0 = nA / S1, f1 = nA / S2, f2 = nB / S3, f3 = nB / S4, f4 = 1.f / (A2 * B2);
  const float co[3][3] = {{h ? f3 : f0, h ? -PB * f3 : PA * f0, h ? B2 * f3 : A2 * f0},
                          {h ? f4 : f1, h ? 0.f : -PA * f1, h ? 0.f : A2 * f1},
                          {h ? 0.f : f2, h ? 0.f : PB * f2, h ? 1.f : B2 * f2}};
#pragma unroll
  for (int p = 0; p < 3; p++) {
    uint32_t o[4];
#pragma unroll
    for (int e = 0; e < 4; e++) {
      float v[2];
#pragma unroll
      for (int q = 0; q < 2; q++) v[q] = co[p][0] * g[0][2 * e + q] + co[p][1] * g[1][2 * e + q] + co[p][2] * g[2][2 * e + q];
      const uint32_t b = pack_bf16(v[0], v[1]);
      o[e] = pack_f16(__uint_as_float(b << 16), __uint_as_float(b & 0xFFFF0000u));
    }
    constexpr uint32_t lim = U_LIM * 0x10001u;
    if (__vimax3_u16x2(__vimax3_u16x2(lim, o[0] & NAN2, o[1] & NAN2), o[2] & NAN2, o[3] & NAN2) != lim) o[0] = NAN2;
    u[p * NSUB * USLAB / 16] = make_uint4(o[0], o[1], o[2], o[3]);
  }
}

constexpr int ROWB = IMG * CH * 2;

__device__ __forceinline__ int region_px(int r) { return (r >> 3) * 8 * IMG + (r & 7) * 64; }
__device__ __forceinline__ int halo_x(int r) { return (r & 7) * 64 - 1; }
__device__ __forceinline__ int halo_y(int r) { return (r >> 3) * 8 - 1; }

__device__ __noinline__ void direct_patch(const __nv_bfloat16* __restrict__ x, const __nv_bfloat16* __restrict__ w,
                                          __nv_bfloat16* __restrict__ out, int y0, int x0, int lane) {
  const int g = lane >> 2, t = lane & 3;
#pragma unroll 1
  for (int k0 = 0; k0 < CH; k0 += 48) {
    float acc[4][6][4] = {};
#pragma unroll 1
    for (int rs = 0; rs < 9; rs++) {
      const int iy = y0 + rs / 3 - 1, ix = x0 + rs % 3 - 1 + g;
#pragma unroll 2
      for (int c = 4 * t; c < CH; c += 16) {
        uint32_t b[6][2];
#pragma unroll
        for (int m = 0; m < 6; m++) {
          const uint32_t* p = (const uint32_t*)(w + (rs * CH + c + (m & 1) * 2) * CH + k0 + (m >> 1) * 16 + 2 * g);
          const uint32_t lo = p[0], hi = p[CH / 2];
          b[m & 6][m & 1] = __byte_perm(lo, hi, 0x5410);
          b[m | 1][m & 1] = __byte_perm(lo, hi, 0x7632);
        }
#pragma unroll
        for (int y = 0; y < 4; y++) {
          uint2 a[2];
#pragma unroll
          for (int h = 0; h < 2; h++)
            a[h] = (unsigned)(iy + y) < IMG && (unsigned)(ix + 8 * h) < IMG ? *(const uint2*)(x + ((iy + y) * IMG + ix + 8 * h) * CH + c)
                                                                           : make_uint2(0, 0);
#pragma unroll
          for (int m = 0; m < 6; m++)
            asm("mma.sync.aligned.m16n8k16.row.col.f32.bf16.bf16.f32 {%0,%1,%2,%3}, {%4,%5,%6,%7}, {%8,%9}, {%0,%1,%2,%3};"
                : "+f"(acc[y][m][0]), "+f"(acc[y][m][1]), "+f"(acc[y][m][2]), "+f"(acc[y][m][3])
                : "r"(a[0].x), "r"(a[1].x), "r"(a[0].y), "r"(a[1].y), "r"(b[m][0]), "r"(b[m][1]));
        }
      }
    }
#pragma unroll
    for (int y = 0; y < 4; y++)
#pragma unroll
      for (int m = 0; m < 6; m += 2)
#pragma unroll
        for (int h = 0; h < 2; h++)
          *(uint2*)(out + ((y0 + y) * IMG + x0 + g + 8 * h) * CH + k0 + m * 8 + 4 * t) =
              make_uint2(pack_bf16(acc[y][m][2 * h], acc[y][m + 1][2 * h]), pack_bf16(acc[y][m][2 * h + 1], acc[y][m + 1][2 * h + 1]));
  }
}

struct Descs { uint64_t a[2][6], b[NSTEP / NU + 1]; };
__host__ __device__ constexpr int slot_use(int i) {
  int c = 0;
  for (int j = 0; j < i; j++) c += vslot(step_p(j), step_n(j)) == vslot(step_p(i), step_n(i));
  return c;
}

__host__ __device__ constexpr int out_time(int q) {
  constexpr int t[24] = {
      49, 50, 51, 52, 54, 55, 56, 57, 59, 60, 61, 63, 64, 65, 66, 68, 69, 70, 72, 73, 75, 76, 78, 79};
  return t[q];
}
__host__ __device__ constexpr int out_at(int t) {
  for (int q = 0; q < 24; q++)
    if (out_time(q) % NSTEP == t) return q;
  return -1;
}
__host__ __device__ constexpr bool out_ok() {
  for (int q = 0; q < 24; q++)
    if (out_time(q) <= last_on(q / 6) || out_time(q) < PIV + (q < 12 ? 4 : 6) || out_time(q) >= first_on(q / 6) + NSTEP ||
        (q && out_time(q) <= out_time(q - 1)))
      return false;
  return true;
}
static_assert(out_ok(), "output plan");
constexpr int OUT_END = out_time(23) + 1 - NSTEP;

struct Consumer {
  uint32_t c1[48], c2[48], c3[48], c4[48];
  const uint64_t *descA, *descB;
  static constexpr uint32_t sb = SMEM_BASE;
  uint8_t* pout;
  int bid, nblk, nlong;
  uint32_t done;
  uint32_t osc, ymax, redo;
  bool lead, ok, odd;

  uint32_t one;
  __device__ __forceinline__ bool always() {
    uint32_t v = one;
    asm volatile("" : "+r"(v));
    return v != 0;
  }
  __device__ __forceinline__ void axpy(uint32_t (&a)[48], uint32_t k, uint32_t (&b)[48]) {
    if (always()) {
      reg_fence(a); reg_fence(b);
#pragma unroll
      for (int i = 0; i < 48; i++) {
        a[i] = hfma2(k, b[i], a[i]);
        if (i % 12 == 11) {
          asm volatile("" : "+r"(a[i])::"memory");
          sched_barrier();
        }
      }
      reg_fence(a);
    }
  }
  uint32_t pa[4], pb[4], px[4];
  __device__ __forceinline__ uint32_t to_bf16(uint32_t h) {
    float lo, hi;
    asm("{\n.reg .b16 l, h;\n.reg .b32 m;\nmov.b32 {l, h}, %3;\ncvt.f32.f16 %0, l;\ncvt.f32.f16 %1, h;\n"
        "abs.f16x2 m, %3;\nmax.NaN.f16x2 %2, m, %2;\n}\n" : "=f"(lo), "=f"(hi), "+r"(ymax) : "r"(h));
    return bmul2(pack_bf16(lo, hi), osc);
  }
  template <int Q, int EXTRA>
  __device__ __forceinline__ void stg(const uint32_t (&v)[4]) {
    constexpr int y = Q < 6 ? 1 : Q < 12 ? 2 : Q < 18 ? 0 : 3;
    asm volatile("st.global.cs.v4.u32 [%0+%5], {%1,%2,%3,%4};" ::"l"(pout), "r"(v[0]), "r"(v[1]), "r"(v[2]), "r"(v[3]),
                 "n"(y * ROWB + (Q / 3) % 2 * 8 * (CH * 2) + Q % 3 * 128 + EXTRA) : "memory");
  }
  template <int Q, bool YIELD>
  __device__ __forceinline__ void convert(uint32_t (&a)[4], uint32_t (&b)[4], uint32_t (&send)[4]) {
    if constexpr (Q >= 0) {
      const uint32_t(&d)[48] = Q < 6 ? c1 : Q < 12 ? c2 : Q < 18 ? c3 : c4;
      constexpr int o = 16 * (Q % 3) + (Q / 3) % 2;
#pragma unroll
      for (int e = 0; e < 4; e++) {
        if (YIELD && e % 2 == 0) sched_barrier();
        a[e] = to_bf16(d[o + 2 * e]);
        b[e] = to_bf16(d[o + 8 + 2 * e]);
        send[e] = odd ? a[e] : b[e];
      }
    }
  }
  template <int QW, int QR, bool STEP>
  __device__ __forceinline__ void output() {
    uint32_t u[4], v[4], a[4], b[4], send[4];
    if constexpr (!STEP) convert<QR, false>(a, b, send);
    sched_barrier();
#pragma unroll
    for (int e = 0; e < 4; e++) {
      u[e] = odd ? px[e] : pa[e];
      v[e] = odd ? pb[e] : px[e];
    }
    if constexpr (STEP) {
      convert<QR, true>(a, b, send);
      asm volatile("{\n.reg .pred p;\nsetp.ne.u32 p, %0, 0;\n@p pmevent 0;\n}" ::"r"((uint32_t)ok) : "memory");
      sched_barrier();
    }
    if constexpr (QW >= 0 && STEP) { stg<QW, 0>(u); stg<QW, CH * 2>(v); }
    if constexpr (QR >= 0) {
#pragma unroll
      for (int e = 0; e < 4; e++) px[e] = __shfl_xor_sync(0xffffffffu, send[e], 4), pa[e] = a[e], pb[e] = b[e];
    }
    if constexpr (QW >= 0 && !STEP) { stg<QW, 0>(u); stg<QW, CH * 2>(v); }
    sched_barrier();
  }
  __device__ __forceinline__ void range_check() {
    const uint32_t m = __reduce_max_sync(0xffffffffu, max(ymax & 0xFFFFu, ymax >> 16));
    redo |= (uint32_t)(m - Y_MIN >= Y_INF - Y_MIN) << done;
    ymax = 0;
  }
  template <int T, int Q0, int Q1, int Q = Q0>
  __device__ __forceinline__ void flush() {
    if constexpr (Q <= Q1) {
      constexpr int QW = Q > Q0 && out_time((Q + 23) % 24) >= T - 1 ? Q - 1 : -1, QR = Q < Q1 && out_time(Q % 24) >= T ? Q : -1;
      if constexpr (QW >= 0 || QR >= 0) output<QW, QR, false>();
      flush<T, Q0, Q1, Q + 1>();
    }
  }
  template <int I>
  __device__ __forceinline__ void hook() {
    constexpr float LP = PB * (PB - PA) / (2.f * A2), LM = PB * (PB + PA) / (2.f * A2);
    constexpr int QW = out_at((I + NSTEP - 1) % NSTEP), QR = out_at(I);
    if constexpr (QW >= 0 || QR >= 0) { if (I > OUT_END || done) output<QW, QR, true>(); }
    if constexpr (I == 20) {
      static_assert(OUT_END < 20, "pointer update");
      range_check();
      osc = lds32(sb + OFF_OSC);
      const int r = bid + done * nblk, d = region_px(r) - region_px(r - nblk);
      asm volatile("mad.wide.s32 %0, %1, 384, %0;" : "+l"(pout) : "r"(d));
    }
    if constexpr (I == 10) { if (bid >= nlong && done == 0 && !(bid & 3)) spin_cycles(24500); }
    if constexpr (I == 42) { if (bid >= nlong && done == 0 && (bid & 3)) spin_cycles(29000); }
    if constexpr (I == PIV) axpy(c1, h2const(S3 * (B2 / A2) / S1), c3);
    if constexpr (I == PIV) axpy(c2, h2const(S3 * (B2 / A2) / S2), c3);
    if constexpr (I == PIV + 1) axpy(c4, h2const(-S3 / S4), c3);
    if constexpr (I == PIV + 1) axpy(c1, h2const(S4 * LP / S1), c4);
    if constexpr (I == PIV + 2) axpy(c2, h2const(S4 * LM / S2), c4);
    if constexpr (I == PIV + 2) axpy(c3, h2const(S4 * (-DD / A2)), c4);
    if constexpr (I == PIV + 3) { axpy(c1, h2const(-1.f / (2.f * PA)), c2); axpy(c2, h2const(PA), c1); }
    if constexpr (I == PIV + 4) axpy(c4, h2const(A2), c1);
    if constexpr (I == PIV + 5) axpy(c3, h2const(1.f / A2), c2);
  }

  template <int I, int END>
  __device__ __forceinline__ void steps() {
    if constexpr (I < END) {
      uint32_t(&d)[48] = step_acc(I) == 0 ? c1 : step_acc(I) == 1 ? c2 : step_acc(I) == 2 ? c3 : c4;
      constexpr int vo = vslot(step_p(I), step_n(I)) * VSLOT, uo = USLOT<I> * USLAB;
      constexpr int J = (I + 1) % NSTEP;
      if (!ok) {
        mbar_wait_short(sb + BAR_UFULL + 8 * USLOT<I>, UUSE<I> & 1);
        if constexpr (first_use(step_n(I)) == I) mbar_wait_short(sb + BAR_VFULL + 8 * (step_n(I) % NB), step_n(I) / NB);
      }
      const uint64_t da = descA[slot_use(I)], db = descB[UUSE<I>];
      wg_fence();
      wgmma192<vo, uo>(d, da, db, first_on(step_acc(I)) == I ? 0u : 1u);
      wgmma192<vo + 16, uo + UTILE>(d, da, db, 1u);
      wgmma192<vo + 32, uo + 2 * UTILE>(d, da, db, 1u);
      wg_commit();
      ok = mbar_test(sb + BAR_UFULL + 8 * USLOT<J>, UUSE<J> & 1);
      if constexpr (first_use(step_n(J)) == J) ok &= mbar_test(sb + BAR_VFULL + 8 * (step_n(J) % NB), step_n(J) / NB);
      hook<I>();
      wg_wait<0>();
      reg_fence(d);
      if (lead) mbar_arrive(sb + BAR_UEMPTY + 8 * USLOT<I>);
      if constexpr (gate_of(I) >= 0) { if (lead) mbar_arrive(sb + BAR_GATE + 8 * (gate_of(I) % NB)); }
      steps<I + 1, END>();
    }
  }
  template <int I>
  __device__ __forceinline__ void chain() {
    if constexpr (I < NSTEP) {
      static_assert(step_acc(I) == 3 && NSTEP - I <= NU, "chain");
      constexpr int vo = vslot(step_p(I), step_n(I)) * VSLOT, uo = USLOT<I> * USLAB;
      mbar_wait_short(sb + BAR_UFULL + 8 * USLOT<I>, UUSE<I> & 1);
      const uint64_t da = descA[5], db = descB[NSTEP / NU];
      wg_fence();
      wgmma192<vo, uo>(c4, da, db, 1u);
      wgmma192<vo + 16, uo + UTILE>(c4, da, db, 1u);
      wgmma192<vo + 32, uo + 2 * UTILE>(c4, da, db, 1u);
      wg_commit();
      chain<I + 1>();
    }
  }
  template <int I>
  __device__ __forceinline__ void release() {
    if constexpr (I < NSTEP) {
      if (lead) mbar_arrive(sb + BAR_UEMPTY + 8 * USLOT<I>);
      release<I + 1>();
    }
  }
  template <int T>
  __device__ __forceinline__ void finish(bool second) {
    if (second) {
      flush<T, 0, 18>();
      asm volatile("bar.sync 1, 256;" ::: "memory");
    }
    chain<T>();
    if (!second) {
      asm volatile("bar.arrive 1, 256;" ::: "memory");
      flush<T, 0, 18>();
    }
    wg_wait<0>();
    reg_fence(c4);
    release<T>();
    done++;
    flush<T, 18, 24>();
  }
};

struct SlotTab { uint32_t off[NSUB][8]; };
constexpr SlotTab make_slots() {
  SlotTab t = {};
  for (int n = 0; n < NSUB; n++)
    for (int p = 0; p < 6; p++) t.off[n][p] = vslot(p, n) * VSLOT;
  return t;
}
__constant__ __align__(64) SlotTab c_slots = make_slots();

constexpr int PF_X = 22, PF_BYTES = PF_X * 2 * 16, PF_NB = 12, U_LEAD = 10;
static_assert(PF_BYTES + 64 <= OFF_U - OFF_SINK, "sink");
__host__ __device__ constexpr uint32_t pf_box(int k) { return 1u << 31 | (k / PF_NB / 3) << 30 | (k / PF_NB % 3) << 28 | (k % PF_NB) << 24; }
__host__ __device__ constexpr int slab_of(int i) { return step_p(i % NSTEP) * NSUB + step_n(i % NSTEP); }
struct LoadTab { uint32_t e[2 * NSTEP]; };
constexpr LoadTab make_loads() {
  LoadTab t = {};
  constexpr int win[6] = {25, 42, 45, 72, 73, 96};
  for (int k = 0, i = 0; k < 6 * PF_NB; k++) {
    const int g = k / PF_NB % 3, when = win[2 * g] + k % PF_NB * (win[2 * g + 1] - win[2 * g]) / PF_NB - (k < 3 * PF_NB ? NSTEP : 0);
    if (when >= 0 && when < NSTEP) t.e[NSTEP + when] = pf_box(k);
    if (k < PF_NB) continue;
    if (i < when) i = when;
    if (i < NSTEP) t.e[i++] = pf_box(k);
  }
  for (int i = 0; i < 2 * NSTEP; i++) {
    int d = 1;
    while (uslot((i + d) % NSTEP) != uslot(i % NSTEP)) d++;
    if (d > NU + 1) d = 0;
    t.e[i] |= (uuse(i % NSTEP) & 1) << 23 | uslot(i % NSTEP) << 20 | d << 16 | slab_of(i + U_LEAD) << 8 | slab_of(i + d);
  }
  return t;
}
__constant__ __align__(64) LoadTab c_load = make_loads();

template <int I>
__device__ __forceinline__ void first_slabs(const uint8_t* u) {
  if constexpr (utrigger(I) < 0) {
    constexpr int slab = slab_of(I);
    load_u_warp(SMEM_BASE + OFF_U + USLOT<I> * USLAB, u + slab * USLAB, SMEM_BASE + BAR_UFULL + 8 * USLOT<I>);
    first_slabs<I + 1>(u);
  }
}

template <int BYTES>
__device__ __forceinline__ uint32_t warm(const void* p, uint32_t zero) {
  uint32_t v = ~0u;
#pragma unroll
  for (int o = 0; o < BYTES; o += 64) v &= ((const uint32_t*)p)[o / 4 + zero];
  return v;
}

__global__ void __launch_bounds__(384, 1) __cluster_dims__(1, 1, 1)
conv_kernel(const __grid_constant__ CUtensorMap tmX, const __grid_constant__ CUtensorMap tmH, const __grid_constant__ CUtensorMap tmP,
            const __nv_bfloat16* __restrict__ xin, const __nv_bfloat16* __restrict__ wgt, __nv_bfloat16* __restrict__ out,
            uint4* ubuf, uint32_t* arrived, int nblk, int nlong, int nmax, const __grid_constant__ Descs desc) {
  extern __shared__ uint8_t smem_raw[];
  const int tid = threadIdx.x, lane = tid & 31, bid = blockIdx.x;
  const int pidx = bid - (nblk - NP);
  constexpr uint32_t sb = SMEM_BASE;
  uint32_t epoch = 0;
  if (tid < 256) {
    cluster_arrive_relaxed();
    if (pidx >= 0) {
      uint32_t t = pidx * 8 + (tid >> 5);
      uint32_t stage = 0, wsm = sb + OFF_V + (tid >> 5) * NROUND * WTASK;
      prep_load(wsm, wgt, t, lane);
      const Sample ws = sample_w(wgt, lane);
      const float sw = __uint_as_float(max(253 - (int)sample_exp(ws), 0) << 23);
      const int klane = (lane & 6) * 4 + (lane >> 3) * 2 + (lane & 1);
#pragma unroll 1
      for (int round = 0; round < NROUND; round++, t += 8 * NP, wsm += WTASK) {
        asm volatile("cp.async.wait_all;" ::: "memory");
        __syncwarp();
        float g[3][8];
#pragma unroll
        for (int i = 0; i < 24; i++) {
          uint16_t v;
          asm volatile("ld.shared.u16 %0, [%1];" : "=h"(v) : "r"(wsm + i * 64 + klane * 2) : "memory");
          g[i / 8][i % 8] = __uint_as_float((uint32_t)v << 16) * sw;
        }
        if (t < NTASK) prep_store(g, ubuf, t, klane);
        if (round + 1 == stage_end(0) || round + 1 == stage_end(1) || round + 1 == NROUND) {
          if (stage == 2) fence_async();
          asm volatile("bar.sync 1, 256;" ::: "memory");
          const uint32_t inc = pidx ? 1 : 0x80000001u - (stage ? NP : 2 * nblk);
          if (stage == 2) asm volatile("ld.relaxed.gpu.global.u32 %0, [%1];" : "=r"(epoch) : "l"(arrived + 64) : "memory");
          if (tid == 0) asm volatile("red.release.gpu.global.add.u32 [%0], %1;" ::"l"(arrived + 32 * stage), "r"(inc) : "memory");
          asm volatile("bar.sync 1, 256;" ::: "memory");
          if (stage++ == 0) {
#pragma unroll 1
            for (int k = 1; k < NROUND; k++) prep_load(wsm + k * WTASK, wgt, t + k * 8 * NP, lane);
          }
        }
      }
      if (tid < 32) asm volatile("bar.arrive 2, 64;" ::: "memory");
    } else if (tid < 32) {
      epoch = stage_enter(arrived, lane);
      spin_until(now(), 2200);
    }
  }
  if (tid >= 352) {
    asm volatile("prefetch.tensormap [%0];" ::"l"(&tmX) : "memory");
    constexpr uint64_t twos = ((2ull << NU) - 1) << (BAR_UEMPTY - OFF_BAR) / 8 | ((1ull << 2 * NB) - 1) << (BAR_VFULL - OFF_BAR) / 8;
    constexpr uint64_t threes = ((1ull << NB) - 1) << (BAR_VFULL - OFF_BAR) / 8;
    if (lane == 0) {
#pragma unroll
      for (int i = 0; i < NBAR; i++) mbar_init(sb + OFF_BAR + 8 * i, 1 + ((twos >> i) & 1) + ((threes >> i) & 1));
      asm volatile("fence.mbarrier_init.release.cluster;" ::: "memory");
      fence_async();
    }
    __syncwarp();
    cluster_arrive_relaxed();
    epoch = stage_enter(arrived, lane);
    if (pidx >= 0) asm volatile("bar.sync 2, 64;" ::: "memory");
    const uint32_t t0 = now();
#pragma unroll 1
    for (int k = 0, box = 0; k < 9; k++, box = box < 6 ? box + 3 : box - 5) {
      if (pidx < 0) spin_until(t0, k * 440);
      tma_box_warp(sb + OFF_X + box * XBOX, k < 8 ? &tmX : &tmH, sb + BAR_XFULL + 8 * box, k < 8 ? XBOX : XHBOX, 0, halo_x(bid) + k * 8,
                   halo_y(bid));
      if (k == 0) asm volatile("prefetch.tensormap [%0];\nprefetch.tensormap [%1];" ::"l"(&tmH), "l"(&tmP) : "memory");
    }
  }
  if (smem_u32(smem_raw) != SMEM_BASE) __trap();
  const int warp = __shfl_sync(0xffffffffu, tid >> 5, 0);

  if (warp < 8) {
    const int wg = warp >> 2;
    if (warp == 7) {
      spin_until(now(), 1300);
      if ((warm<sizeof(SlotTab)>(&c_slots, tid >> 10) & warm<sizeof(LoadTab)>(&c_load, tid >> 10)) == ~0u) __trap();
    }
    cluster_wait();
    if (warp == 0) {
      stage_wait(arrived, __shfl_sync(0xffffffffu, epoch, 0));
      first_slabs<0>((const uint8_t*)ubuf);
    }
    asm volatile("setmaxnreg.inc.sync.aligned.u32 224;");
    Consumer c;
#pragma unroll
    for (int i = 0; i < 48; i++) { c.c1[i] = 0; c.c2[i] = 0; c.c3[i] = 0; c.c4[i] = 0; }
#pragma unroll
    for (int e = 0; e < 4; e++) c.pa[e] = c.pb[e] = c.px[e] = 0;
    c.descA = desc.a[wg];
    c.descB = desc.b;
    c.lead = (tid & 127) == 0;
    c.one = __shfl_sync(0xffffffffu, nblk, 0);
    c.ok = false;
    c.bid = bid;
    c.nblk = nblk;
    c.nlong = nlong;
    c.odd = (lane >> 2) & 1;
    c.pout = (uint8_t*)out + (long long)(region_px(bid - nblk) + wg * 4 * IMG + (warp & 3) * 16 + (lane >> 3) * 2) * (CH * 2) + (lane & 7) * 16;
    c.done = c.osc = c.ymax = c.redo = 0;
    constexpr int ROT = 69;
    bool tail = false;
#pragma unroll 1
    do {
      wg_wait<0>();
      if (tail) {
        c.steps<ROT, NSTEP>();
        c.done++;
      }
      c.steps<0, ROT>();
      tail = c.always();
    } while (bid + (int)(c.done + 1) * nblk < NREG);
    c.finish<ROT>(wg);
    c.range_check();
    if (c.redo >> 1) {
      __syncwarp();
      for (int i = 0; i < (int)c.done; i++)
        if ((c.redo >> (i + 1)) & 1) {
          const int r = bid + i * nblk;
          direct_patch(xin, wgt, out, (r >> 3) * 8 + wg * 4, (r & 7) * 64 + (warp & 3) * 16, lane);
        }
    }
  } else {
    asm volatile("setmaxnreg.dec.sync.aligned.u32 56;");
    const int nitem = nmax - (bid >= nlong);
    if (warp == 11) {
      const uint8_t* ubase = (const uint8_t*)ubuf;
      epoch = __shfl_sync(0xffffffffu, epoch, 0);
      cluster_wait();
      const uint8_t* uline = ubase + (bid * 2 + lane) * 128;
      const bool ufetch = lane < 2 && bid < USLAB / 256;
      int r = bid, npf = 0;
      int i = 0, tab = 0;
#pragma unroll 1
      for (int left = nitem * NSTEP - 1; left >= 0; left--) {
        const uint32_t e = c_load.e[tab + i], slot = (e >> 20) & 7;
        const uint8_t* src = ubase + (e & 255) * USLAB;
        const uint8_t* pu = uline + ((e >> 8) & 255) * USLAB;
        const uint32_t dst = sb + OFF_U + slot * USLAB, ebar = sb + BAR_UEMPTY + 8 * slot;
        const bool refill = ((e >> 16) & 7) - 1 < (uint32_t)left;
        constexpr int need1 = utrigger(stage_first(1)), need2 = utrigger(stage_first(2)), xslab = slab_of(UX_FIRST);
        if (tab + i == need1 || tab + i == need2) stage_wait(arrived + (i == need1 ? 32 : 64), epoch);
        refill_u(ebar, (e >> 23) & 1, refill, dst, src);
        if (i == UX_GATE) load_u_warp(sb + OFF_V, ubase + xslab * USLAB, sb + BAR_UFULL + 8 * NU);
        const int rr = r + ((e >> 30) & 1) * nblk;
        if ((int)e < 0 && rr < NREG) {
          asm volatile("{\n.reg .pred p;\nelect.sync _|p, 0xffffffff;\n"
                       "@p cp.async.bulk.tensor.3d.shared::cluster.global.mbarrier::complete_tx::bytes [%0], [%1, {%3, %4, %5}], [%2];\n}\n"
                       ::"r"(sb + OFF_SINK), "l"(&tmP), "r"(sb + BAR_SINK), "r"((e >> 22) & 0xC0), "r"(halo_x(rr) + ((e >> 26) & 3) * PF_X),
                       "r"(halo_y(rr) + 1 + ((e >> 23) & 6)) : "memory");
          npf++;
        }
        if (ufetch && tab + i >= NSTEP - U_LEAD && left >= U_LEAD)
          asm volatile("cp.async.ca.shared.global.L2::128B [%0], [%1], 4;" ::"r"(sb + OFF_SINK + PF_BYTES + lane * 4), "l"(pu) : "memory");
        if (++i == NSTEP) { i = 0; r += nblk; tab = NSTEP; }
      }
      if (lane == 0) asm volatile("mbarrier.arrive.expect_tx.shared::cta.b64 _, [%0], %1;" ::"r"(sb + BAR_SINK), "r"(npf * PF_BYTES) : "memory");
      mbar_wait(sb + BAR_SINK, 0);
      asm volatile("cp.async.wait_all;" ::: "memory");
    } else {
      cluster_arrive_relaxed();
      const int w = warp - 8, col = (lane >> 1) & 7, chunk = lane >> 4;
      const uint32_t xbox = sb + OFF_X + w * 3 * XBOX, xbar = sb + BAR_XFULL + 24 * w;
      const uint32_t xl = xbox + col * 32 + ((chunk ^ (col >> 2)) << 4) + (lane & 1) * 8;
      const uint32_t vl = sb + OFF_V + chunk * VROW + w * 128 + (lane & 15) * 8;
      const bool in_row = w < 2 || col < 2;
      const uint32_t pitch2 = w < 2 ? 256 : 64, bytes2 = 10 * pitch2;
      const uint32_t xl2 = w < 2 ? xl + 2 * XBOX : xbox + 2 * XBOX + col * 32 + chunk * 16 + (lane & 1) * 8;
      const CUtensorMap* tm2 = w < 2 ? &tmX : &tmH;
      auto xrow = [&](int j, int i) {
        uint2 v = make_uint2(0, 0);
        if (j < 2 || in_row) v = lds64(j < 2 ? xl + j * XBOX + i * 256 : xl2 + i * pitch2);
        return v;
      };
      const Sample ws = sample_w(wgt, lane), xs = sample_x(xin, bid, lane);
      uint32_t xsc;
      {
        const int ex = sample_exp(xs), eo = ex + (int)sample_exp(ws) - (111 + X_EXP), es = 127 + X_EXP - ex;
        xsc = es >= 1 && eo >= 1 && eo <= 254 ? es * 0x00800080u : NAN2;
        asm volatile("st.shared.u32 [%0], %1;" ::"r"(sb + OFF_OSC), "r"(eo * 0x00800080u) : "memory");
      }
      constexpr uint32_t gate_par = [] { uint32_t m = 0; for (int n = 0; n < NSUB; n++) if ((n / NB) ^ (gate(n % NB) < 0)) m |= 1u << n; return m; }();
      constexpr uint32_t LIM2 = X_LIM * 0x10001u;
      cluster_wait();
      auto conv = [&](uint2& v, uint32_t m) {
        const uint32_t tx = bmul2(v.x, xsc), ty = bmul2(v.y, xsc), ux = tx & NAN2, uy = ty & NAN2;
        v = make_uint2(ux * 7 + tx, uy * 7 + ty);
        return __vimax3_u16x2(m, ux, uy);
      };
      uint32_t so[6] = {};
      auto planes = [&](const uint2* h, uint32_t m, uint32_t a, bool on) {
        constexpr uint32_t NB2 = h2const(-B2), NA2 = h2const(-A2);
        const uint2 e1 = fma4(NB2, h[2], h[4]), e2 = fma4(NA2, h[2], h[4]);
        store_v(a + so[4], fma4(NA2, fma4(NB2, h[0], h[2]), e1), on);
        const uint2 o1 = fma4(NB2, h[1], h[3]), o2 = fma4(NA2, h[1], h[3]);
        store_v(a + so[5], fma4(NA2, o1, fma4(NB2, h[3], h[5])), on);
        uint2 v = fma4(h2const(PA), o1, e1);
        if (m != LIM2) v.x = NAN2;
        store_v(a + so[0], v, on);
        store_v(a + so[1], fma4(h2const(-PA), o1, e1), on);
        store_v(a + so[2], fma4(h2const(PB), o2, e2), on);
        store_v(a + so[3], fma4(h2const(-PB), o2, e2), on);
      };
      int r = bid, n = 0;
      uint32_t par = 0;
#pragma unroll 1
      for (int left = nitem * NSUB; left > 0; left--) {
        const int nb = n >= NB ? n - NB : n;
        uint2 d[10];
        mbar_wait(xbar, par);
#pragma unroll
        for (int i = 0; i < 6; i++) d[i] = xrow(0, i);
#pragma unroll
        for (int p = 0; p < 6; p++) so[p] = c_slots.off[n][p];
        const uint32_t gpar = (gate_par >> n) & 1;
        if (++n == NSUB) { n = 0; r += nblk; }
        const int fc = n * 16, fx = halo_x(r) + w * 8, fy = halo_y(r);
#pragma unroll
        for (int j = 0; j < 3; j++) {
          const bool on = j < 2 || in_row;
#pragma unroll
          for (int i = 6; i < 10; i++) d[i] = xrow(j, i);
          const bool xok = j < 2 && mbar_test(xbar + 8 * (j + 1), par);
          sched_barrier();
          const uint32_t m45 = conv(d[5], conv(d[4], LIM2));
          const uint32_t ma = conv(d[3], conv(d[1], conv(d[0], conv(d[2], m45))));
          if (j == 0) mbar_wait(sb + BAR_GATE + 8 * nb, gpar);
          planes(d, ma, vl + j * 384, on);
          sched_barrier();
          const uint32_t mb = conv(d[9], conv(d[7], conv(d[6], conv(d[8], m45))));
          if (left > 1) tma_box_warp(xbox + j * XBOX, j < 2 ? &tmX : tm2, xbar + 8 * j, (j < 2 ? XBOX : bytes2) | (mb & 0x8000u), fc, fx + j * 24, fy);
          uint2 h[6];
#pragma unroll
          for (int i = 0; i < 6; i++) h[i] = d[4 + i];
          if (j < 2) {
            mbar_wait(xbar + 8 * (j + 1), par, xok);
#pragma unroll
            for (int i = 0; i < 6; i++) d[i] = xrow(j + 1, i);
          }
          sched_barrier();
          planes(h, mb, vl + j * 384 + VPIECE, on);
          sched_barrier();
        }
        fence_async();
        asm volatile("{\n.reg .pred p;\nelect.sync _|p, 0xffffffff;\n@p mbarrier.arrive.shared::cta.b64 _, [%0];\n}\n" ::"r"(sb + BAR_VFULL + 8 * nb) : "memory");
        par ^= 1;
      }
    }
  }
}

constexpr uint64_t make_desc(uint32_t off, uint32_t lbo, uint32_t sbo) {
  return (uint64_t)((SMEM_BASE + off) >> 4) | ((uint64_t)(lbo >> 4) << 16) | ((uint64_t)(sbo >> 4) << 32);
}

typedef CUresult (*EncodeFn)(CUtensorMap*, CUtensorMapDataType, cuuint32_t, void*, const cuuint64_t*, const cuuint64_t*,
                             const cuuint32_t*, const cuuint32_t*, CUtensorMapInterleave, CUtensorMapSwizzle,
                             CUtensorMapL2promotion, CUtensorMapFloatOOBfill);

}

extern "C" void kernel_launch(void* const* d_in, const int* in_sizes, int n_in, void* d_out, int out_size) {
  static EncodeFn enc = nullptr;
  static int nblk = 0;
  static uint4* ubuf;
  static uint32_t* arrived;
  if (!enc) {
    cudaGetSymbolAddress((void**)&ubuf, g_U);
    cudaGetSymbolAddress((void**)&arrived, g_arrived);
    cudaDriverEntryPointQueryResult qr;
    cudaGetDriverEntryPoint("cuTensorMapEncodeTiled", (void**)&enc, cudaEnableDefault, &qr);
    cudaFuncSetAttribute(conv_kernel, cudaFuncAttributeMaxDynamicSharedMemorySize, SMEM_BYTES);
    int dev;
    cudaGetDevice(&dev);
    cudaDeviceGetAttribute(&nblk, cudaDevAttrMultiProcessorCount, dev);
  }
  CUtensorMap tmX, tmH, tmP;
  const cuuint64_t dims[3] = {CH, IMG, IMG};
  const cuuint64_t strides[2] = {CH * 2, (cuuint64_t)CH * 2 * IMG};
  const cuuint32_t es[3] = {1, 1, 1};
  const cuuint32_t boxX[3] = {16, 8, 10}, boxH[3] = {16, 2, 10}, boxP[3] = {8, PF_X, 2};
  enc(&tmH, CU_TENSOR_MAP_DATA_TYPE_BFLOAT16, 3, d_in[0], dims, strides, boxH, es, CU_TENSOR_MAP_INTERLEAVE_NONE,
      CU_TENSOR_MAP_SWIZZLE_NONE, CU_TENSOR_MAP_L2_PROMOTION_L2_64B, CU_TENSOR_MAP_FLOAT_OOB_FILL_NONE);
  enc(&tmP, CU_TENSOR_MAP_DATA_TYPE_BFLOAT16, 3, d_in[0], dims, strides, boxP, es, CU_TENSOR_MAP_INTERLEAVE_NONE,
      CU_TENSOR_MAP_SWIZZLE_NONE, CU_TENSOR_MAP_L2_PROMOTION_L2_128B, CU_TENSOR_MAP_FLOAT_OOB_FILL_NONE);
  enc(&tmX, CU_TENSOR_MAP_DATA_TYPE_BFLOAT16, 3, d_in[0], dims, strides, boxX, es, CU_TENSOR_MAP_INTERLEAVE_NONE,
      CU_TENSOR_MAP_SWIZZLE_32B, CU_TENSOR_MAP_L2_PROMOTION_L2_64B, CU_TENSOR_MAP_FLOAT_OOB_FILL_NONE);
  Descs desc = {};
  for (int i = 0; i < 6; i++) { desc.a[0][i] = make_desc(OFF_V, VROW, 128); desc.a[1][i] = make_desc(OFF_V + VPIECE, VROW, 128); }
  for (int i = 0; i <= NSTEP / NU; i++) desc.b[i] = make_desc(OFF_U, 128, 256);
  conv_kernel<<<nblk, 384, SMEM_BYTES>>>(tmX, tmH, tmP, (const __nv_bfloat16*)d_in[0], (const __nv_bfloat16*)d_in[1], (__nv_bfloat16*)d_out, ubuf, arrived, nblk,
                                         NREG % nblk ? NREG % nblk : nblk, (NREG + nblk - 1) / nblk, desc);
}
```

```cpp
#include <cuda_runtime.h>
#include <cuda_bf16.h>
#include <cuda.h>
#include <stdint.h>

namespace {

constexpr int IMG = 512, CH = 192;
constexpr float PA = 0.6875f, PB = 1.5f;
constexpr float A2 = PA * PA, B2 = PB * PB, DD = B2 - A2;

constexpr int NSTEP = 72, NSUB = 12;
__host__ __device__ constexpr int sched(int i) {
  constexpr int t[NSTEP] = {
      0x00, 0x10, 0x20, 0x01, 0x11, 0x21, 0x02, 0x12, 0x22, 0x03, 0x13, 0x23, 0x30, 0x31, 0x32, 0x33, 0x24, 0x34,
      0x04, 0x14, 0x25, 0x35, 0x05, 0x15, 0x26, 0x36, 0x06, 0x16, 0x27, 0x37, 0x07, 0x17, 0x28, 0x38, 0x08, 0x18,
      0x29, 0x39, 0x09, 0x19, 0x2a, 0x3a, 0x0a, 0x1a, 0x2b, 0x3b, 0x1b, 0x0b, 0x40, 0x4b, 0x50, 0x41, 0x51, 0x4a,
      0x49, 0x48, 0x47, 0x42, 0x52, 0x46, 0x45, 0x5b, 0x44, 0x43, 0x5a, 0x53, 0x59, 0x58, 0x57, 0x56, 0x54, 0x55};
  return t[i];
}
__host__ __device__ constexpr int step_p(int i) { return sched(i) >> 4; }
__host__ __device__ constexpr int step_n(int i) { return sched(i) & 15; }
__host__ __device__ constexpr int step_acc(int i) { return step_p(i) < 4 ? step_p(i) : step_p(i) - 2; }
__host__ __device__ constexpr int first_on(int acc) {
  for (int i = 0; i < NSTEP; i++)
    if (step_acc(i) == acc) return i;
  return -1;
}
__host__ __device__ constexpr int last_on(int acc) {
  for (int i = NSTEP - 1; i >= 0; i--)
    if (step_acc(i) == acc) return i;
  return -1;
}
__host__ __device__ constexpr int find_step(int p, int n) {
  for (int i = 0; i < NSTEP; i++)
    if (sched(i) == p * 16 + n) return i;
  return -1;
}
__host__ __device__ constexpr int first_use(int n) {
  for (int i = 0; i < NSTEP; i++)
    if (step_n(i) == n) return i;
  return -1;
}
constexpr int NHEAD = first_on(3) / 3 * 4;
__host__ __device__ constexpr int head(int i) { return i < NHEAD ? find_step(i % 4, i / 4) : i; }
constexpr float S1 = 1.f / PA, S2 = 1.f / (2.f * A2), S3 = -A2 / (2.f * DD), S4 = -1.f / (PB * DD);
constexpr int PIV = find_step(3, NSUB - 1);
static_assert(find_step(2, NSUB - 1) == PIV - 1 && last_on(1) == PIV + 1 && last_on(0) == PIV + 2 && PIV + 3 == 4 * NSUB &&
              step_p(PIV + 3) == 4 && step_p(PIV + 4) == 4 && step_p(PIV + 5) == 5, "basis change");

constexpr int NV = 32, NB = 6;
__host__ __device__ constexpr int vslot(int p, int n) {
  constexpr int t[6][NSUB] = {
      {31, 19, 25, 18, 19, 27, 21, 4, 24, 26, 3, 26}, {28, 23, 24, 22, 17, 24, 28, 3, 25, 27, 0, 28}, {27, 17, 14,
      20, 23, 22, 20, 31, 0, 28, 1, 2}, {26, 21, 15, 16, 31, 18, 23, 26, 23, 31, 4, 31}, {7, 6, 8, 10, 12, 14, 15,
      17, 19, 21, 23, 27}, {30, 29, 9, 11, 13, 5, 16, 18, 20, 22, 24, 25}};
  return t[p][n];
}
__host__ __device__ constexpr int gate(int n) {
  constexpr int t[NSUB] = {-20, -14, -8, -2, 5, 11, 16, 21, 25, 29, 34, 39};
  return t[n];
}
__host__ __device__ constexpr int gate_of(int i) {
  for (int n = 0; n < NSUB; n++)
    if ((gate(n) + NSTEP) % NSTEP == i) return n;
  return -1;
}
__host__ __device__ constexpr int head_gate_of(int i) {
  for (int n = 0; n < NSUB; n++) {
    int m = -1;
    for (int j = 0; j < NHEAD; j++)
      if (head(j) <= gate(n)) m = j;
    if (gate(n) < NHEAD && m == i) return n;
  }
  return -1;
}
__host__ __device__ constexpr bool gates_ok() {
  int early = 0;
  for (int i = 0; i < NHEAD; i++) early += (gate_of(i) >= 0) - (head_gate_of(i) >= 0) + (head(i) >= NHEAD);
  if (early) return false;
  for (int n = 0; n < NSUB; n++) {
    for (int p = 0; p < 6; p++)
      for (int d = 1; d <= NSUB; d++)
        for (int q = 0; q < 6; q++) {
          const int m = (n - d + NSUB) % NSUB;
          if (vslot(q, m) == vslot(p, n) && (find_step(q, m) - (n - d < 0 ? NSTEP : 0) > gate(n) || (m == n && p != q))) return false;
        }
    if (n > 0 && (gate(n) <= gate(n - 1) || first_use(n) <= first_use(n - 1))) return false;
    if (gate(n) >= first_use(n)) return false;
    if (gate((n + NB) % NSUB) + (n >= NB ? NSTEP : 0) < first_use(n)) return false;
  }
  return gate(0) + NSTEP > gate(NSUB - 1) && gate(NB) >= 0;
}
static_assert(gates_ok(), "gates");

constexpr int UTILE = CH * 16 * 2;
constexpr int USLAB = 3 * UTILE;
constexpr int NU = 4;
constexpr int VROW = 66 * 16;
constexpr int VPIECE = 2 * VROW;
constexpr int VSLOT = 2 * VPIECE;
constexpr int XBOX = 10 * 8 * 32;
constexpr int XHBOX = 10 * 2 * 32;
constexpr int UX_FIRST = 52, UX_COUNT = 8, UX_GATE = UX_FIRST - NU - 1;
__host__ __device__ constexpr bool uextra(int i) {
  const int d = (i - UX_FIRST + NSTEP) % NSTEP;
  return d % (NU + 1) == 0 && d / (NU + 1) < UX_COUNT;
}
__host__ __device__ constexpr int uindex(int i) {
  int c = 0;
  for (int j = 0; j < i; j++) c += uextra(j) == uextra(i);
  return c;
}
__host__ __device__ constexpr int uslot(int i) { return uextra(i) ? NU : uindex(i) % NU; }
__host__ __device__ constexpr int uuse(int i) { return uextra(i) ? uindex(i) : uindex(i) / NU; }
__host__ __device__ constexpr int utrigger(int j) {
  if (j == UX_FIRST) return UX_GATE;
  int i = j - 1;
  while (uslot((i + NSTEP) % NSTEP) != uslot(j)) i--;
  return i;
}
template <int I> constexpr int USLOT = uslot(I);
template <int I> constexpr int UUSE = uuse(I);
__host__ __device__ constexpr bool uring_ok() {
  for (int n = 0; n < NSUB; n++)
    for (int p = 0; p < 6; p++)
      if (vslot(p, n) * VSLOT < USLAB &&
          (find_step(p, n) > UX_GATE || gate(n) < UX_FIRST + (NU + 1) * (UX_COUNT - 1) - NSTEP))
        return false;
  return UX_COUNT % 2 == 0 && (NSTEP - UX_COUNT) % (2 * NU) == 0;
}
static_assert(uring_ok(), "U ring");

constexpr int OFF_X = 0;
constexpr int OFF_SINK = OFF_X + 8 * XBOX + XHBOX;
constexpr int OFF_U = OFF_SINK + 768;
constexpr int OFF_V = OFF_U + NU * USLAB;
constexpr int OFF_BAR = OFF_V + NV * VSLOT;
constexpr int BAR_UFULL = OFF_BAR;
constexpr int BAR_UEMPTY = BAR_UFULL + 8 * (NU + 1);
constexpr int BAR_XFULL = BAR_UEMPTY + 8 * (NU + 1);
constexpr int BAR_VFULL = BAR_XFULL + 8 * 9;
constexpr int BAR_GATE = BAR_VFULL + 8 * NB;
constexpr int BAR_SINK = BAR_GATE + 8 * NB;
constexpr int OFF_OSC = BAR_SINK + 8;
constexpr int NBAR = (OFF_OSC - OFF_BAR) / 8;
constexpr int SMEM_BYTES = OFF_OSC + 8;
constexpr uint32_t SMEM_BASE = 1024;
static_assert(SMEM_BYTES <= 232448, "smem");

constexpr int NREG = 512;

__device__ __align__(128) uint4 g_U[NSTEP * USLAB / 16];
__device__ uint32_t g_arrived[3 * 32];

__device__ __forceinline__ uint32_t smem_u32(const void* p) { return (uint32_t)__cvta_generic_to_shared(p); }
__device__ __forceinline__ void mbar_init(uint32_t a, int c) {
  asm volatile("mbarrier.init.shared::cta.b64 [%0], %1;" ::"r"(a), "r"(c) : "memory");
}
__device__ __forceinline__ void mbar_arrive(uint32_t a) {
  asm volatile("mbarrier.arrive.shared::cta.b64 _, [%0];" ::"r"(a) : "memory");
}
__device__ __forceinline__ void mbar_wait(uint32_t a, uint32_t parity, uint32_t skip = 0) {
  asm volatile(
      "{\n"
      ".reg .pred p;\n"
      ".reg .u32 n;\n"
      "setp.ne.u32 p, %2, 0;\n"
      "@p bra.uni LAB_DONE;\n"
      "mov.u32 n, 0;\n"
      "LAB_WAIT:\n"
      "mbarrier.try_wait.parity.shared::cta.b64 p, [%0], %1;\n"
      "@p bra.uni LAB_DONE;\n"
      "add.u32 n, n, 1;\n"
      "setp.lt.u32 p, n, 4000000;\n"
      "@p bra.uni LAB_WAIT;\n"
      "trap;\n"
      "LAB_DONE:\n"
      "}\n" ::"r"(a), "r"(parity), "r"(skip) : "memory");
}
__device__ __forceinline__ void mbar_wait_short(uint32_t a, uint32_t parity) {
  asm volatile("{\n.reg .pred p;\nLAB_WAIT:\nmbarrier.try_wait.parity.shared::cta.b64 p, [%0], %1;\n@!p bra.uni LAB_WAIT;\n}\n" ::"r"(a),
               "r"(parity) : "memory");
}
__device__ __forceinline__ bool mbar_test(uint32_t a, uint32_t parity) {
  uint32_t ok;
  asm volatile("{\n.reg .pred p;\nmbarrier.test_wait.parity.shared::cta.b64 p, [%1], %2;\nselp.u32 %0, 1, 0, p;\n}\n"
               : "=r"(ok) : "r"(a), "r"(parity) : "memory");
  return ok;
}
__device__ __forceinline__ void fence_async() { asm volatile("fence.proxy.async.shared::cta;" ::: "memory"); }
__device__ __forceinline__ void tma_box_warp(uint32_t dst, const CUtensorMap* tm, uint32_t bar, uint32_t bytes, int c, int x, int y) {
  asm volatile(
      "{\n.reg .pred p;\nelect.sync _|p, 0xffffffff;\n"
      "@p mbarrier.arrive.expect_tx.shared::cta.b64 _, [%2], %6;\n"
      "@p cp.async.bulk.tensor.3d.shared::cluster.global.mbarrier::complete_tx::bytes [%0], [%1, {%3, %4, %5}], [%2];\n}\n" ::"r"(dst),
      "l"(tm), "r"(bar), "r"(c), "r"(x), "r"(y), "r"(bytes) : "memory");
}
__device__ __forceinline__ void load_u_warp(uint32_t dst, const void* src, uint32_t bar) {
  asm volatile("{\n.reg .pred p;\nelect.sync _|p, 0xffffffff;\n"
               "@p mbarrier.arrive.expect_tx.shared::cta.b64 _, [%2], %3;\n"
               "@p cp.async.bulk.shared::cluster.global.mbarrier::complete_tx::bytes [%0], [%1], %3, [%2];\n}\n" ::"r"(dst),
               "l"(src), "r"(bar), "n"(USLAB) : "memory");
}
__device__ __forceinline__ void refill_u(uint32_t ebar, uint32_t parity, uint32_t on, uint32_t dst, const void* src) {
  asm volatile(
      "{\n.reg .pred p;\n.reg .u32 n;\n"
      "mov.u32 n, 0;\n"
      "LAB_WAIT:\n"
      "mbarrier.try_wait.parity.shared::cta.b64 p, [%0], %1;\n"
      "@p bra.uni LAB_DONE;\n"
      "add.u32 n, n, 1;\nsetp.lt.u32 p, n, 4000000;\n"
      "@p bra.uni LAB_WAIT;\n"
      "trap;\n"
      "LAB_DONE:\n"
      "setp.eq.u32 p, %2, 0;\n"
      "@p bra.uni LAB_OUT;\n"
      "elect.sync _|p, 0xffffffff;\n"
      "@p mbarrier.arrive.expect_tx.shared::cta.b64 _, [%5], %6;\n"
      "@p cp.async.bulk.shared::cluster.global.mbarrier::complete_tx::bytes [%3], [%4], %6, [%5];\n"
      "LAB_OUT:\n}\n" ::"r"(ebar), "r"(parity), "r"(on), "r"(dst), "l"(src), "r"(ebar - (BAR_UEMPTY - BAR_UFULL)), "n"(USLAB) : "memory");
}
__device__ __forceinline__ uint2 lds64(uint32_t a) {
  uint2 v;
  asm volatile("ld.shared.v2.u32 {%0,%1}, [%2];" : "=r"(v.x), "=r"(v.y) : "r"(a) : "memory");
  return v;
}
__device__ __forceinline__ uint32_t lds32(uint32_t a) {
  uint32_t v;
  asm volatile("ld.shared.u32 %0, [%1];" : "=r"(v) : "r"(a) : "memory");
  return v;
}
__device__ __forceinline__ void store_v(uint32_t a, uint2 v, bool on) {
  v.x &= 0xFFFCFFFCu; v.y &= 0xFFFCFFFCu;
  if (on) asm volatile("st.shared.v2.u32 [%0], {%1,%2};" ::"r"(a), "r"(v.x), "r"(v.y) : "memory");
}
__device__ __forceinline__ void sched_barrier() { asm volatile("pmevent 0;" ::: "memory"); }
__device__ __forceinline__ void spin_cycles(uint32_t n) {
  asm volatile(
      "{\n.reg .pred p;\n.reg .u32 t0, t;\n"
      "mov.u32 t0, %%clock;\n"
      "LAB_SPIN:\n"
      "nanosleep.u32 50;\n"
      "mov.u32 t, %%clock;\nsub.u32 t, t, t0;\nsetp.lt.u32 p, t, %0;\n"
      "@p bra.uni LAB_SPIN;\n}\n" ::"r"(n) : "memory");
}
__device__ __forceinline__ void spin_until(uint32_t t0, uint32_t n) {
  asm volatile("{\n.reg .pred p;\n.reg .u32 t;\nLAB_SPIN:\nmov.u32 t, %%clock;\nsub.u32 t, t, %0;\nsetp.lt.u32 p, t, %1;\n@p bra.uni LAB_SPIN;\n}\n" ::"r"(t0),
               "r"(n) : "memory");
}
__device__ __forceinline__ uint32_t now() {
  uint32_t t;
  asm volatile("mov.u32 %0, %%clock;" : "=r"(t)::"memory");
  return t;
}
__device__ __forceinline__ uint32_t stage_enter(uint32_t* ctr, int lane) {
  uint32_t old;
  asm volatile("{\n.reg .pred p;\nsetp.eq.u32 p, %2, 0;\nld.relaxed.gpu.global.u32 %0, [%1];\n@p red.relaxed.gpu.global.add.u32 [%1], %3;\n}"
               : "=r"(old) : "l"(ctr), "r"(lane), "r"(lane + 1) : "memory");
  return old;
}
__device__ __forceinline__ void stage_wait(const uint32_t* ctr, uint32_t old) {
  asm volatile(
      "{\n.reg .pred p;\n.reg .u32 v, i;\n"
      "mov.u32 i, 0;\n"
      "LAB_POLL:\n"
      "ld.acquire.gpu.global.u32 v, [%0];\n"
      "xor.b32 v, v, %1;\nsetp.lt.s32 p, v, 0;\n"
      "@p bra.uni LAB_OUT;\n"
      "add.u32 i, i, 1;\nsetp.lt.u32 p, i, 4000000;\n"
      "@p bra.uni LAB_POLL;\n"
      "trap;\n"
      "LAB_OUT:\n"
      "fence.proxy.async.global;\n}\n" ::"l"(ctr), "r"(old) : "memory");
}
__device__ __forceinline__ void cluster_arrive_relaxed() { asm volatile("barrier.cluster.arrive.relaxed.aligned;" ::: "memory"); }
__device__ __forceinline__ void cluster_wait() { asm volatile("barrier.cluster.wait.acquire.aligned;" ::: "memory"); }

__host__ __device__ constexpr uint32_t h2const(float v) {
  double a = v < 0 ? -v : v;
  int e = 15;
  while (a >= 2) { a /= 2; e++; }
  while (a < 1) { a *= 2; e--; }
  const uint32_t h = (v < 0 ? 0x8000u : 0u) | ((e << 10) + (uint32_t)((a - 1) * 1024 + 0.5));
  return h | h << 16;
}
__device__ __forceinline__ uint32_t hfma2(uint32_t a, uint32_t b, uint32_t c) {
  uint32_t d;
  asm("fma.rn.f16x2 %0, %1, %2, %3;" : "=r"(d) : "r"(a), "r"(b), "r"(c));
  return d;
}
__device__ __forceinline__ uint32_t bmul2(uint32_t a, uint32_t b) {
  uint32_t d;
  asm("mul.rn.bf16x2 %0, %1, %2;" : "=r"(d) : "r"(a), "r"(b));
  return d;
}
__device__ __forceinline__ uint2 fma4(uint32_t k, const uint2& a, const uint2& c) { return make_uint2(hfma2(k, a.x, c.x), hfma2(k, a.y, c.y)); }
__device__ __forceinline__ uint32_t pack_bf16(float lo, float hi) {
  uint32_t d;
  asm("cvt.rn.bf16x2.f32 %0, %1, %2;" : "=r"(d) : "f"(hi), "f"(lo));
  return d;
}
__device__ __forceinline__ uint32_t pack_f16(float lo, float hi) {
  uint32_t d;
  asm("cvt.rn.f16x2.f32 %0, %1, %2;" : "=r"(d) : "f"(hi), "f"(lo));
  return d;
}

template <int AOFF, int BOFF>
__device__ __forceinline__ void wgmma192(uint32_t (&d)[48], uint64_t da, uint64_t db, uint32_t scale_d) {
  asm volatile(
      "{\n.reg .pred p;\n.reg .b64 qa, qb;\n"
      "setp.ne.b32 p, %50, 0;\n"
      "add.s64 qa, %48, %51;\nadd.s64 qb, %49, %52;\n"
      "wgmma.mma_async.sync.aligned.m64n192k16.f16.f16.f16 "
      "{%0, %1, %2, %3, %4, %5, %6, %7, %8, %9, %10, %11, %12, %13, %14, %15, "
      "%16, %17, %18, %19, %20, %21, %22, %23, %24, %25, %26, %27, %28, %29, %30, %31, "
      "%32, %33, %34, %35, %36, %37, %38, %39, %40, %41, %42, %43, %44, %45, %46, %47}, "
      "qa, qb, p, 1, 1, 0, 0;\n}\n"
      : "+r"(d[0]), "+r"(d[1]), "+r"(d[2]), "+r"(d[3]), "+r"(d[4]), "+r"(d[5]), "+r"(d[6]), "+r"(d[7]), "+r"(d[8]),
        "+r"(d[9]), "+r"(d[10]), "+r"(d[11]), "+r"(d[12]), "+r"(d[13]), "+r"(d[14]), "+r"(d[15]), "+r"(d[16]),
        "+r"(d[17]), "+r"(d[18]), "+r"(d[19]), "+r"(d[20]), "+r"(d[21]), "+r"(d[22]), "+r"(d[23]), "+r"(d[24]),
        "+r"(d[25]), "+r"(d[26]), "+r"(d[27]), "+r"(d[28]), "+r"(d[29]), "+r"(d[30]), "+r"(d[31]), "+r"(d[32]),
        "+r"(d[33]), "+r"(d[34]), "+r"(d[35]), "+r"(d[36]), "+r"(d[37]), "+r"(d[38]), "+r"(d[39]), "+r"(d[40]),
        "+r"(d[41]), "+r"(d[42]), "+r"(d[43]), "+r"(d[44]), "+r"(d[45]), "+r"(d[46]), "+r"(d[47])
      : "l"(da), "l"(db), "r"(scale_d), "n"(AOFF >> 4), "n"(BOFF >> 4));
}
__device__ __forceinline__ void wg_fence() { asm volatile("wgmma.fence.sync.aligned;" ::: "memory"); }
__device__ __forceinline__ void wg_commit() { asm volatile("wgmma.commit_group.sync.aligned;" ::: "memory"); }
template <int N>
__device__ __forceinline__ void wg_wait() { asm volatile("wgmma.wait_group.sync.aligned %0;" ::"n"(N) : "memory"); }
__device__ __forceinline__ void reg_fence(uint32_t (&d)[48]) {
#pragma unroll
  for (int i = 0; i < 48; i++) asm volatile("" : "+r"(d[i])::"memory");
}

constexpr uint32_t X_EXP = 17;
constexpr uint32_t X_LIM = ((15 + 8) << 7) - 1;
constexpr uint32_t U_LIM = ((15 + 6) << 10) - 1;
constexpr uint32_t Y_MIN = 0x3C00, Y_INF = 0x7C00;
constexpr uint32_t NAN2 = 0x7FFF7FFFu;
using Sample = uint4;
__device__ __forceinline__ uint4 ldg128(const uint4* p) {
  uint4 v;
  asm volatile("ld.global.v4.u32 {%0,%1,%2,%3}, [%4];" : "=r"(v.x), "=r"(v.y), "=r"(v.z), "=r"(v.w) : "l"(p));
  return v;
}
__device__ __forceinline__ Sample sample_w(const __nv_bfloat16* w, int lane) {
  const int q = lane >> 3;
  return ldg128((const uint4*)(w + ((q == 0 ? 1 : q == 1 ? 3 : 4) * CH + 47 * q) * CH + 64 * (q % 3)) + (lane & 7));
}
__device__ __forceinline__ Sample sample_x(const __nv_bfloat16* x, int r, int lane) {
  return ldg128((const uint4*)(x + (size_t)(((r >> 3) * 8 + 1 + lane % 6) * IMG + (r & 7) * 64 + 2 * lane) * CH) + lane % 24);
}
__device__ __forceinline__ uint32_t sample_exp(const Sample& s) {
  const uint32_t m = __vmaxu2(__vimax3_u16x2(s.x & NAN2, s.y & NAN2, s.z & NAN2), s.w & NAN2);
  return __reduce_max_sync(0xffffffffu, max(m & 0xFFFFu, m >> 16)) >> 7;
}

constexpr int NP = 16, NTASK = 24 * 36, NROUND = (NTASK + 8 * NP - 1) / (8 * NP);
__host__ __device__ constexpr int stage_end(int k) { return k == 0 ? 1 : k == 1 ? 3 : NROUND; }
__host__ __device__ constexpr int stage_first(int k) {
  for (int i = 0; i < NSTEP; i++) {
    const int g = step_p(head(i)) / 4 * NSUB + step_n(head(i));
    if ((g + 1) * 36 > stage_end(k - 1) * 8 * NP) return i;
  }
  return -1;
}
static_assert(utrigger(stage_first(1)) >= 0 && stage_first(2) > stage_first(1), "stages");
struct Task {
  uint32_t n, s, kh, k;
  bool h;
  __device__ __forceinline__ Task(uint32_t t, int lane) {
    const uint32_t grp = t / 36, sub = t % 36;
    h = grp >= NSUB;
    n = h ? grp - NSUB : grp;
    s = sub / 12, kh = (sub / 6) & 1, k = sub % 6 * 32 + lane;
  }
};
constexpr int WTASK = 24 * 64;
__device__ __forceinline__ void prep_load(uint32_t dst, const __nv_bfloat16* __restrict__ w, uint32_t t, int lane) {
  const Task q(min(t, NTASK - 1), 0);
  w += ((q.s * 24 + 2 * q.n + q.kh) * 8 + (lane >> 2)) * CH + q.k + (lane & 3) * 8;
#pragma unroll
  for (int r = 0; r < 3; r++)
    asm volatile("cp.async.cg.shared.global [%0], [%1], 16;" ::"r"(dst + r * 512 + lane * 16), "l"(w + r * 3 * CH * CH) : "memory");
}
__device__ __forceinline__ void prep_store(const float (&g)[3][8], uint4* u, uint32_t t, int lane) {
  const Task q(t, lane);
  const uint32_t n = q.n, s = q.s, kh = q.kh, k = q.k;
  const bool h = q.h;
  const uint32_t jn = (k >> 5) * 4 + ((k >> 1) & 3), row = ((k >> 3) & 3) * 2 + (k & 1);
  u += (((h ? 4 * NSUB : 0) + n) * USLAB + s * UTILE + jn * 256 + kh * 128 + row * 16) >> 4;
  constexpr float nA = -1.f / (2.f * A2 * DD), nB = 1.f / (2.f * B2 * DD);
  constexpr float f0 = nA / S1, f1 = nA / S2, f2 = nB / S3, f3 = nB / S4, f4 = 1.f / (A2 * B2);
  const float co[4][3] = {{h ? f4 : f0, h ? 0.f : PA * f0, h ? 0.f : A2 * f0},
                          {h ? 0.f : f1, h ? 0.f : -PA * f1, h ? 1.f : A2 * f1},
                          {f2, PB * f2, B2 * f2},
                          {f3, -PB * f3, B2 * f3}};
#pragma unroll
  for (int p = 0; p < 4; p++) {
    if (p == 2 && h) break;
    uint32_t o[4];
#pragma unroll
    for (int e = 0; e < 4; e++) {
      float v[2];
#pragma unroll
      for (int q = 0; q < 2; q++) v[q] = co[p][0] * g[0][2 * e + q] + co[p][1] * g[1][2 * e + q] + co[p][2] * g[2][2 * e + q];
      const uint32_t b = pack_bf16(v[0], v[1]);
      o[e] = pack_f16(__uint_as_float(b << 16), __uint_as_float(b & 0xFFFF0000u));
    }
    constexpr uint32_t lim = U_LIM * 0x10001u;
    if (__vimax3_u16x2(__vimax3_u16x2(lim, o[0] & NAN2, o[1] & NAN2), o[2] & NAN2, o[3] & NAN2) != lim) o[0] = NAN2;
    u[p * NSUB * USLAB / 16] = make_uint4(o[0], o[1], o[2], o[3]);
  }
}

constexpr int ROWB = IMG * CH * 2;

__device__ __forceinline__ int region_px(int r) { return (r >> 3) * 8 * IMG + (r & 7) * 64; }
__device__ __forceinline__ int halo_x(int r) { return (r & 7) * 64 - 1; }
__device__ __forceinline__ int halo_y(int r) { return (r >> 3) * 8 - 1; }

__device__ __noinline__ void direct_patch(const __nv_bfloat16* __restrict__ x, const __nv_bfloat16* __restrict__ w,
                                          __nv_bfloat16* __restrict__ out, int y0, int x0, int lane) {
  const int g = lane >> 2, t = lane & 3;
#pragma unroll 1
  for (int k0 = 0; k0 < CH; k0 += 48) {
    float acc[4][6][4] = {};
#pragma unroll 1
    for (int rs = 0; rs < 9; rs++) {
      const int iy = y0 + rs / 3 - 1, ix = x0 + rs % 3 - 1 + g;
#pragma unroll 2
      for (int c = 4 * t; c < CH; c += 16) {
        uint32_t b[6][2];
#pragma unroll
        for (int m = 0; m < 6; m++) {
          const uint32_t* p = (const uint32_t*)(w + (rs * CH + c + (m & 1) * 2) * CH + k0 + (m >> 1) * 16 + 2 * g);
          const uint32_t lo = p[0], hi = p[CH / 2];
          b[m & 6][m & 1] = __byte_perm(lo, hi, 0x5410);
          b[m | 1][m & 1] = __byte_perm(lo, hi, 0x7632);
        }
#pragma unroll
        for (int y = 0; y < 4; y++) {
          uint2 a[2];
#pragma unroll
          for (int h = 0; h < 2; h++)
            a[h] = (unsigned)(iy + y) < IMG && (unsigned)(ix + 8 * h) < IMG ? *(const uint2*)(x + ((iy + y) * IMG + ix + 8 * h) * CH + c)
                                                                           : make_uint2(0, 0);
#pragma unroll
          for (int m = 0; m < 6; m++)
            asm("mma.sync.aligned.m16n8k16.row.col.f32.bf16.bf16.f32 {%0,%1,%2,%3}, {%4,%5,%6,%7}, {%8,%9}, {%0,%1,%2,%3};"
                : "+f"(acc[y][m][0]), "+f"(acc[y][m][1]), "+f"(acc[y][m][2]), "+f"(acc[y][m][3])
                : "r"(a[0].x), "r"(a[1].x), "r"(a[0].y), "r"(a[1].y), "r"(b[m][0]), "r"(b[m][1]));
        }
      }
    }
#pragma unroll
    for (int y = 0; y < 4; y++)
#pragma unroll
      for (int m = 0; m < 6; m += 2)
#pragma unroll
        for (int h = 0; h < 2; h++)
          *(uint2*)(out + ((y0 + y) * IMG + x0 + g + 8 * h) * CH + k0 + m * 8 + 4 * t) =
              make_uint2(pack_bf16(acc[y][m][2 * h], acc[y][m + 1][2 * h]), pack_bf16(acc[y][m][2 * h + 1], acc[y][m + 1][2 * h + 1]));
  }
}

struct Descs { uint64_t a[2][6], b[22]; };
__host__ __device__ constexpr int slot_use(int i) {
  int c = 0;
  for (int j = 0; j < i; j++) c += vslot(step_p(j), step_n(j)) == vslot(step_p(i), step_n(i));
  return c;
}

__host__ __device__ constexpr int out_time(int q) {
  constexpr int t[24] = {
      49, 50, 51, 52, 54, 55, 56, 57, 59, 60, 61, 63, 64, 65, 66, 68, 69, 70, 72, 74, 76, 78, 80, 82};
  return t[q];
}
__host__ __device__ constexpr int out_at(int t) {
  for (int q = 0; q < 24; q++)
    if (out_time(q) % NSTEP == t) return q;
  return -1;
}
__host__ __device__ constexpr bool out_ok() {
  for (int q = 0; q < 24; q++)
    if (out_time(q) <= last_on(q / 6) || out_time(q) < PIV + (q < 12 ? 4 : 6) || out_time(q) >= first_on(q / 6) + NSTEP ||
        (q && out_time(q) <= out_time(q - 1)))
      return false;
  return true;
}
static_assert(out_ok(), "output plan");
constexpr int OUT_END = out_time(23) + 1 - NSTEP;

struct Consumer {
  uint32_t c1[48], c2[48], c3[48], c4[48];
  const uint64_t *descA, *descB;
  static constexpr uint32_t sb = SMEM_BASE;
  uint8_t* pout;
  int bid, nblk, nlong;
  uint32_t done;
  uint32_t osc, ymax, redo;
  bool lead, ok, odd;

  uint32_t one;
  __device__ __forceinline__ bool always() {
    uint32_t v = one;
    asm volatile("" : "+r"(v));
    return v != 0;
  }
  __device__ __forceinline__ void axpy(uint32_t (&a)[48], uint32_t k, uint32_t (&b)[48]) {
    if (always()) {
      reg_fence(a); reg_fence(b);
#pragma unroll
      for (int i = 0; i < 48; i++) {
        a[i] = hfma2(k, b[i], a[i]);
        if (i % 12 == 11) {
          asm volatile("" : "+r"(a[i])::"memory");
          sched_barrier();
        }
      }
      reg_fence(a);
    }
  }
  uint32_t pa[4], pb[4], px[4];
  __device__ __forceinline__ uint32_t to_bf16(uint32_t h) {
    float lo, hi;
    asm("{\n.reg .b16 l, h;\n.reg .b32 m;\nmov.b32 {l, h}, %3;\ncvt.f32.f16 %0, l;\ncvt.f32.f16 %1, h;\n"
        "abs.f16x2 m, %3;\nmax.NaN.f16x2 %2, m, %2;\n}\n" : "=f"(lo), "=f"(hi), "+r"(ymax) : "r"(h));
    return bmul2(pack_bf16(lo, hi), osc);
  }
  template <int Q, int EXTRA>
  __device__ __forceinline__ void stg(const uint32_t (&v)[4]) {
    constexpr int y = Q < 6 ? 1 : Q < 12 ? 2 : Q < 18 ? 0 : 3;
    asm volatile("st.global.cs.v4.u32 [%0+%5], {%1,%2,%3,%4};" ::"l"(pout), "r"(v[0]), "r"(v[1]), "r"(v[2]), "r"(v[3]),
                 "n"(y * ROWB + (Q / 3) % 2 * 8 * (CH * 2) + Q % 3 * 128 + EXTRA) : "memory");
  }
  template <int Q, bool YIELD>
  __device__ __forceinline__ void convert(uint32_t (&a)[4], uint32_t (&b)[4], uint32_t (&send)[4]) {
    if constexpr (Q >= 0) {
      const uint32_t(&d)[48] = Q < 6 ? c1 : Q < 12 ? c2 : Q < 18 ? c3 : c4;
      constexpr int o = 16 * (Q % 3) + (Q / 3) % 2;
#pragma unroll
      for (int e = 0; e < 4; e++) {
        if (YIELD && e % 2 == 0) sched_barrier();
        a[e] = to_bf16(d[o + 2 * e]);
        b[e] = to_bf16(d[o + 8 + 2 * e]);
        send[e] = odd ? a[e] : b[e];
      }
    }
  }
  template <int QW, int QR, bool STEP>
  __device__ __forceinline__ void output() {
    uint32_t u[4], v[4], a[4], b[4], send[4];
    if constexpr (!STEP) convert<QR, false>(a, b, send);
    sched_barrier();
#pragma unroll
    for (int e = 0; e < 4; e++) {
      u[e] = odd ? px[e] : pa[e];
      v[e] = odd ? pb[e] : px[e];
    }
    if constexpr (STEP) {
      convert<QR, true>(a, b, send);
      asm volatile("{\n.reg .pred p;\nsetp.ne.u32 p, %0, 0;\n@p pmevent 0;\n}" ::"r"((uint32_t)ok) : "memory");
      sched_barrier();
    }
    if constexpr (QW >= 0 && STEP) { stg<QW, 0>(u); stg<QW, CH * 2>(v); }
    if constexpr (QR >= 0) {
#pragma unroll
      for (int e = 0; e < 4; e++) px[e] = __shfl_xor_sync(0xffffffffu, send[e], 4), pa[e] = a[e], pb[e] = b[e];
    }
    if constexpr (QW >= 0 && !STEP) { stg<QW, 0>(u); stg<QW, CH * 2>(v); }
    sched_barrier();
  }
  __device__ __forceinline__ void range_check() {
    const uint32_t m = __reduce_max_sync(0xffffffffu, max(ymax & 0xFFFFu, ymax >> 16));
    redo |= (uint32_t)(m - Y_MIN >= Y_INF - Y_MIN) << done;
    ymax = 0;
  }
  template <int T, int Q0, int Q1, int Q = Q0>
  __device__ __forceinline__ void flush() {
    if constexpr (Q <= Q1) {
      constexpr int QW = Q > Q0 && out_time((Q + 23) % 24) >= T - 1 ? Q - 1 : -1, QR = Q < Q1 && out_time(Q % 24) >= T ? Q : -1;
      if constexpr (QW >= 0 || QR >= 0) output<QW, QR, false>();
      flush<T, Q0, Q1, Q + 1>();
    }
  }
  template <int I>
  __device__ __forceinline__ void hook() {
    constexpr float LP = PB * (PB - PA) / (2.f * A2), LM = PB * (PB + PA) / (2.f * A2);
    constexpr int QW = out_at((I + NSTEP - 1) % NSTEP), QR = out_at(I);
    if constexpr (QW >= 0 || QR >= 0) output<QW, QR, true>();
    if constexpr (I == 22) {
      static_assert(OUT_END < NHEAD, "pointer update");
      range_check();
      osc = lds32(sb + OFF_OSC);
      const int r = bid + done * nblk, d = region_px(r) - region_px(r - nblk);
      asm volatile("mad.wide.s32 %0, %1, 384, %0;" : "+l"(pout) : "r"(d));
    }
    if constexpr (I == NHEAD) { if (bid >= nlong && done == 0 && !(bid & 3)) spin_cycles(24500); }
    if constexpr (I == 42) { if (bid >= nlong && done == 0 && (bid & 3)) spin_cycles(28000); }
    if constexpr (I == PIV) axpy(c1, h2const(S3 * (B2 / A2) / S1), c3);
    if constexpr (I == PIV) axpy(c2, h2const(S3 * (B2 / A2) / S2), c3);
    if constexpr (I == PIV + 1) axpy(c4, h2const(-S3 / S4), c3);
    if constexpr (I == PIV + 1) axpy(c1, h2const(S4 * LP / S1), c4);
    if constexpr (I == PIV + 2) axpy(c2, h2const(S4 * LM / S2), c4);
    if constexpr (I == PIV + 2) axpy(c3, h2const(S4 * (-DD / A2)), c4);
    if constexpr (I == PIV + 3) { axpy(c1, h2const(-1.f / (2.f * PA)), c2); axpy(c2, h2const(PA), c1); }
    if constexpr (I == PIV + 4) axpy(c4, h2const(A2), c1);
    if constexpr (I == PIV + 5) axpy(c3, h2const(1.f / A2), c2);
  }

  template <int I, int END, bool FIRST = false>
  __device__ __forceinline__ void steps() {
    if constexpr (I < END) {
      constexpr int J = (I + 1) % NSTEP, S = FIRST ? head(I) : I, T = FIRST ? head(J) : J, G = FIRST ? head_gate_of(I) : gate_of(I);
      uint32_t(&d)[48] = step_acc(S) == 0 ? c1 : step_acc(S) == 1 ? c2 : step_acc(S) == 2 ? c3 : c4;
      constexpr int vo = vslot(step_p(S), step_n(S)) * VSLOT, uo = USLOT<I> * USLAB;
      if (!ok) {
        mbar_wait_short(sb + BAR_UFULL + 8 * USLOT<I>, UUSE<I> & 1);
        if constexpr (first_use(step_n(S)) == S) mbar_wait_short(sb + BAR_VFULL + 8 * (step_n(S) % NB), step_n(S) / NB);
      }
      const uint64_t da = descA[FIRST ? 4 : slot_use(I)], db = descB[(FIRST ? 16 : 0) + UUSE<I>];
      wg_fence();
      wgmma192<vo, uo>(d, da, db, first_on(step_acc(S)) == S ? 0u : 1u);
      wgmma192<vo + 16, uo + UTILE>(d, da, db, 1u);
      wgmma192<vo + 32, uo + 2 * UTILE>(d, da, db, 1u);
      wg_commit();
      ok = mbar_test(sb + BAR_UFULL + 8 * USLOT<J>, UUSE<J> & 1);
      if constexpr (first_use(step_n(T)) == T) ok &= mbar_test(sb + BAR_VFULL + 8 * (step_n(T) % NB), step_n(T) / NB);
      if constexpr (!FIRST) hook<I>();
      wg_wait<0>();
      reg_fence(d);
      if (lead) mbar_arrive(sb + BAR_UEMPTY + 8 * USLOT<I>);
      if constexpr (G >= 0) { if (lead) mbar_arrive(sb + BAR_GATE + 8 * (G % NB)); }
      steps<I + 1, END, FIRST>();
    }
  }
  template <int I>
  __device__ __forceinline__ void chain() {
    if constexpr (I < NSTEP) {
      static_assert(step_acc(I) == 3 && NSTEP - I <= NU, "chain");
      constexpr int vo = vslot(step_p(I), step_n(I)) * VSLOT, uo = USLOT<I> * USLAB;
      mbar_wait_short(sb + BAR_UFULL + 8 * USLOT<I>, UUSE<I> & 1);
      const uint64_t da = descA[5], db = descB[21];
      wg_fence();
      wgmma192<vo, uo>(c4, da, db, 1u);
      wgmma192<vo + 16, uo + UTILE>(c4, da, db, 1u);
      wgmma192<vo + 32, uo + 2 * UTILE>(c4, da, db, 1u);
      wg_commit();
      chain<I + 1>();
    }
  }
  template <int I>
  __device__ __forceinline__ void release() {
    if constexpr (I < NSTEP) {
      if (lead) mbar_arrive(sb + BAR_UEMPTY + 8 * USLOT<I>);
      release<I + 1>();
    }
  }
  template <int T>
  __device__ __forceinline__ void finish(bool second) {
    if (second) {
      flush<T, 0, 18>();
      asm volatile("bar.sync 1, 256;" ::: "memory");
    }
    chain<T>();
    if (!second) {
      asm volatile("bar.arrive 1, 256;" ::: "memory");
      flush<T, 0, 18>();
    }
    wg_wait<0>();
    reg_fence(c4);
    release<T>();
    done++;
    flush<T, 18, 24>();
  }
};

struct SlotTab { uint32_t off[NSUB][8]; };
constexpr SlotTab make_slots() {
  SlotTab t = {};
  for (int n = 0; n < NSUB; n++)
    for (int p = 0; p < 6; p++) t.off[n][p] = vslot(p, n) * VSLOT;
  return t;
}
__constant__ __align__(64) SlotTab c_slots = make_slots();

constexpr int PF_X = 22, PF_BYTES = PF_X * 2 * 16, PF_NB = 12, U_LEAD = 10;
static_assert(PF_BYTES + 64 <= OFF_U - OFF_SINK, "sink");
__host__ __device__ constexpr uint32_t pf_box(int k) { return 1u << 31 | (k / PF_NB / 3) << 30 | (k / PF_NB % 3) << 28 | (k % PF_NB) << 24; }
__host__ __device__ constexpr int slab_of(int i) { return step_p(i % NSTEP) * NSUB + step_n(i % NSTEP); }
struct LoadTab { uint32_t e[2 * NSTEP]; };
constexpr LoadTab make_loads() {
  LoadTab t = {};
  constexpr int win[6] = {25, 42, 45, 72, 73, 96};
  for (int k = 0, i = 0; k < 6 * PF_NB; k++) {
    const int g = k / PF_NB % 3, when = win[2 * g] + k % PF_NB * (win[2 * g + 1] - win[2 * g]) / PF_NB - (k < 3 * PF_NB ? NSTEP : 0);
    if (when >= 0 && when < NSTEP) t.e[NSTEP + when] = pf_box(k);
    if (k < PF_NB) continue;
    if (i < when) i = when;
    if (i < NSTEP) t.e[i++] = pf_box(k);
  }
  for (int i = 0; i < 2 * NSTEP; i++) {
    int d = 1;
    while (uslot((i + d) % NSTEP) != uslot(i % NSTEP)) d++;
    if (d > NU + 1) d = 0;
    t.e[i] |= (uuse(i % NSTEP) & 1) << 23 | uslot(i % NSTEP) << 20 | d << 16 | slab_of(i + U_LEAD) << 8 | slab_of(head(i + d));
  }
  return t;
}
__constant__ __align__(64) LoadTab c_load = make_loads();

template <int I>
__device__ __forceinline__ void first_slabs(const uint8_t* u) {
  if constexpr (utrigger(I) < 0) {
    constexpr int slab = slab_of(head(I));
    load_u_warp(SMEM_BASE + OFF_U + USLOT<I> * USLAB, u + slab * USLAB, SMEM_BASE + BAR_UFULL + 8 * USLOT<I>);
    first_slabs<I + 1>(u);
  }
}

template <int BYTES>
__device__ __forceinline__ uint32_t warm(const void* p, uint32_t zero) {
  uint32_t v = ~0u;
#pragma unroll
  for (int o = 0; o < BYTES; o += 64) v &= ((const uint32_t*)p)[o / 4 + zero];
  return v;
}

__global__ void __launch_bounds__(384, 1) __cluster_dims__(1, 1, 1)
conv_kernel(const __grid_constant__ CUtensorMap tmX, const __grid_constant__ CUtensorMap tmH, const __grid_constant__ CUtensorMap tmP,
            const __nv_bfloat16* __restrict__ xin, const __nv_bfloat16* __restrict__ wgt, __nv_bfloat16* __restrict__ out,
            uint4* ubuf, uint32_t* arrived, int nblk, int nlong, int nmax, const __grid_constant__ Descs desc) {
  extern __shared__ uint8_t smem_raw[];
  const int tid = threadIdx.x, lane = tid & 31, bid = blockIdx.x;
  const int pidx = bid - (nblk - NP);
  constexpr uint32_t sb = SMEM_BASE;
  uint32_t epoch = 0;
  if (tid < 256) {
    cluster_arrive_relaxed();
    if (pidx >= 0) {
      uint32_t t = pidx * 8 + (tid >> 5);
      uint32_t stage = 0, wsm = sb + OFF_V + (tid >> 5) * NROUND * WTASK;
      prep_load(wsm, wgt, t, lane);
      const Sample ws = sample_w(wgt, lane);
      const float sw = __uint_as_float(max(253 - (int)sample_exp(ws), 0) << 23);
      const int klane = (lane & 6) * 4 + (lane >> 3) * 2 + (lane & 1);
#pragma unroll 1
      for (int round = 0; round < NROUND; round++, t += 8 * NP, wsm += WTASK) {
        asm volatile("cp.async.wait_all;" ::: "memory");
        __syncwarp();
        float g[3][8];
#pragma unroll
        for (int i = 0; i < 24; i++) {
          uint16_t v;
          asm volatile("ld.shared.u16 %0, [%1];" : "=h"(v) : "r"(wsm + i * 64 + klane * 2) : "memory");
          g[i / 8][i % 8] = __uint_as_float((uint32_t)v << 16) * sw;
        }
        if (t < NTASK) prep_store(g, ubuf, t, klane);
        if (round + 1 == stage_end(0) || round + 1 == stage_end(1) || round + 1 == NROUND) {
          if (stage == 2) fence_async();
          asm volatile("bar.sync 1, 256;" ::: "memory");
          const uint32_t inc = pidx ? 1 : 0x80000001u - (stage ? NP : 2 * nblk);
          if (stage == 2) asm volatile("ld.relaxed.gpu.global.u32 %0, [%1];" : "=r"(epoch) : "l"(arrived + 64) : "memory");
          if (tid == 0) asm volatile("red.release.gpu.global.add.u32 [%0], %1;" ::"l"(arrived + 32 * stage), "r"(inc) : "memory");
          asm volatile("bar.sync 1, 256;" ::: "memory");
          if (stage++ == 0) {
#pragma unroll 1
            for (int k = 1; k < NROUND; k++) prep_load(wsm + k * WTASK, wgt, t + k * 8 * NP, lane);
          }
        }
      }
      if (tid < 32) asm volatile("bar.arrive 2, 64;" ::: "memory");
    } else if (tid < 32) {
      epoch = stage_enter(arrived, lane);
      spin_until(now(), 2200);
    }
  }
  if (tid >= 352) {
    asm volatile("prefetch.tensormap [%0];" ::"l"(&tmX) : "memory");
    constexpr uint64_t twos = ((2ull << NU) - 1) << (BAR_UEMPTY - OFF_BAR) / 8 | ((1ull << 2 * NB) - 1) << (BAR_VFULL - OFF_BAR) / 8;
    constexpr uint64_t threes = ((1ull << NB) - 1) << (BAR_VFULL - OFF_BAR) / 8;
    if (lane == 0) {
#pragma unroll
      for (int i = 0; i < NBAR; i++) mbar_init(sb + OFF_BAR + 8 * i, 1 + ((twos >> i) & 1) + ((threes >> i) & 1));
      asm volatile("fence.mbarrier_init.release.cluster;" ::: "memory");
      fence_async();
    }
    __syncwarp();
    cluster_arrive_relaxed();
    epoch = stage_enter(arrived, lane);
    if (pidx >= 0) asm volatile("bar.sync 2, 64;" ::: "memory");
    const uint32_t t0 = now();
#pragma unroll 1
    for (int k = 0, box = 0; k < 9; k++, box = box < 6 ? box + 3 : box - 5) {
      if (pidx < 0) spin_until(t0, min(k, 7) * 520);
      tma_box_warp(sb + OFF_X + box * XBOX, k < 8 ? &tmX : &tmH, sb + BAR_XFULL + 8 * box, k < 8 ? XBOX : XHBOX, 0, halo_x(bid) + k * 8,
                   halo_y(bid));
      if (k == 0) asm volatile("prefetch.tensormap [%0];\nprefetch.tensormap [%1];" ::"l"(&tmH), "l"(&tmP) : "memory");
    }
  }
  if (smem_u32(smem_raw) != SMEM_BASE) __trap();
  const int warp = __shfl_sync(0xffffffffu, tid >> 5, 0);

  if (warp < 8) {
    const int wg = warp >> 2;
    if (warp == 7) {
      spin_until(now(), 1300);
      if ((warm<sizeof(SlotTab)>(&c_slots, tid >> 10) & warm<sizeof(LoadTab)>(&c_load, tid >> 10)) == ~0u) __trap();
    }
    cluster_wait();
    if (warp == 0) {
      stage_wait(arrived, __shfl_sync(0xffffffffu, epoch, 0));
      first_slabs<0>((const uint8_t*)ubuf);
    }
    asm volatile("setmaxnreg.inc.sync.aligned.u32 224;");
    Consumer c;
#pragma unroll
    for (int i = 0; i < 48; i++) { c.c1[i] = 0; c.c2[i] = 0; c.c3[i] = 0; c.c4[i] = 0; }
#pragma unroll
    for (int e = 0; e < 4; e++) c.pa[e] = c.pb[e] = c.px[e] = 0;
    c.descA = desc.a[wg];
    c.descB = desc.b;
    c.lead = (tid & 127) == 0;
    c.one = __shfl_sync(0xffffffffu, nblk, 0);
    c.ok = false;
    c.bid = bid;
    c.nblk = nblk;
    c.nlong = nlong;
    c.odd = (lane >> 2) & 1;
    c.pout = (uint8_t*)out + (long long)(region_px(bid - nblk) + wg * 4 * IMG + (warp & 3) * 16 + (lane >> 3) * 2) * (CH * 2) + (lane & 7) * 16;
    c.done = c.osc = c.ymax = c.redo = 0;
    constexpr int ROT = 69;
    c.steps<0, NHEAD, true>();
    bool tail = false;
#pragma unroll 1
    do {
      wg_wait<0>();
      if (tail) {
        c.steps<ROT, NSTEP>();
        c.done++;
        c.steps<0, NHEAD>();
      }
      c.steps<NHEAD, ROT>();
      tail = c.always();
    } while (bid + (int)(c.done + 1) * nblk < NREG);
    c.finish<ROT>(wg);
    c.range_check();
    if (c.redo >> 1) {
      __syncwarp();
      for (int i = 0; i < (int)c.done; i++)
        if ((c.redo >> (i + 1)) & 1) {
          const int r = bid + i * nblk;
          direct_patch(xin, wgt, out, (r >> 3) * 8 + wg * 4, (r & 7) * 64 + (warp & 3) * 16, lane);
        }
    }
  } else {
    asm volatile("setmaxnreg.dec.sync.aligned.u32 56;");
    const int nitem = nmax - (bid >= nlong);
    if (warp == 11) {
      const uint8_t* ubase = (const uint8_t*)ubuf;
      epoch = __shfl_sync(0xffffffffu, epoch, 0);
      cluster_wait();
      const uint8_t* uline = ubase + (bid * 2 + lane) * 128;
      const bool ufetch = lane < 2 && bid < USLAB / 256;
      int r = bid, npf = 0;
      int i = 0, tab = 0;
#pragma unroll 1
      for (int left = nitem * NSTEP - 1; left >= 0; left--) {
        const uint32_t e = c_load.e[tab + i], slot = (e >> 20) & 7;
        const uint8_t* src = ubase + (e & 255) * USLAB;
        const uint8_t* pu = uline + ((e >> 8) & 255) * USLAB;
        const uint32_t dst = sb + OFF_U + slot * USLAB, ebar = sb + BAR_UEMPTY + 8 * slot;
        const bool refill = ((e >> 16) & 7) - 1 < (uint32_t)left;
        constexpr int need1 = utrigger(stage_first(1)), need2 = utrigger(stage_first(2)), xslab = slab_of(UX_FIRST);
        if (tab + i == need1 || tab + i == need2) stage_wait(arrived + (i == need1 ? 32 : 64), epoch);
        refill_u(ebar, (e >> 23) & 1, refill, dst, src);
        if (i == UX_GATE) load_u_warp(sb + OFF_V, ubase + xslab * USLAB, sb + BAR_UFULL + 8 * NU);
        const int rr = r + ((e >> 30) & 1) * nblk;
        if ((int)e < 0 && rr < NREG) {
          asm volatile("{\n.reg .pred p;\nelect.sync _|p, 0xffffffff;\n"
                       "@p cp.async.bulk.tensor.3d.shared::cluster.global.mbarrier::complete_tx::bytes [%0], [%1, {%3, %4, %5}], [%2];\n}\n"
                       ::"r"(sb + OFF_SINK), "l"(&tmP), "r"(sb + BAR_SINK), "r"((e >> 22) & 0xC0), "r"(halo_x(rr) + ((e >> 26) & 3) * PF_X),
                       "r"(halo_y(rr) + 1 + ((e >> 23) & 6)) : "memory");
          npf++;
        }
        if (ufetch && tab + i >= NSTEP - U_LEAD && left >= U_LEAD)
          asm volatile("cp.async.ca.shared.global.L2::128B [%0], [%1], 4;" ::"r"(sb + OFF_SINK + PF_BYTES + lane * 4), "l"(pu) : "memory");
        if (++i == NSTEP) { i = 0; r += nblk; tab = NSTEP; }
      }
      if (lane == 0) asm volatile("mbarrier.arrive.expect_tx.shared::cta.b64 _, [%0], %1;" ::"r"(sb + BAR_SINK), "r"(npf * PF_BYTES) : "memory");
      mbar_wait(sb + BAR_SINK, 0);
      asm volatile("cp.async.wait_all;" ::: "memory");
    } else {
      cluster_arrive_relaxed();
      const int w = warp - 8, col = (lane >> 1) & 7, chunk = lane >> 4;
      const uint32_t xbox = sb + OFF_X + w * 3 * XBOX, xbar = sb + BAR_XFULL + 24 * w;
      const uint32_t xl = xbox + col * 32 + ((chunk ^ (col >> 2)) << 4) + (lane & 1) * 8;
      const uint32_t vl = sb + OFF_V + chunk * VROW + w * 128 + (lane & 15) * 8;
      const bool in_row = w < 2 || col < 2;
      const uint32_t pitch2 = w < 2 ? 256 : 64, bytes2 = 10 * pitch2;
      const uint32_t xl2 = w < 2 ? xl + 2 * XBOX : xbox + 2 * XBOX + col * 32 + chunk * 16 + (lane & 1) * 8;
      const CUtensorMap* tm2 = w < 2 ? &tmX : &tmH;
      auto xrow = [&](int j, int i) {
        uint2 v = make_uint2(0, 0);
        if (j < 2 || in_row) v = lds64(j < 2 ? xl + j * XBOX + i * 256 : xl2 + i * pitch2);
        return v;
      };
      const Sample ws = sample_w(wgt, lane), xs = sample_x(xin, bid, lane);
      uint32_t xsc;
      {
        const int ex = sample_exp(xs), eo = ex + (int)sample_exp(ws) - (111 + X_EXP), es = 127 + X_EXP - ex;
        xsc = es >= 1 && eo >= 1 && eo <= 254 ? es * 0x00800080u : NAN2;
        asm volatile("st.shared.u32 [%0], %1;" ::"r"(sb + OFF_OSC), "r"(eo * 0x00800080u) : "memory");
      }
      constexpr uint32_t gate_par = [] { uint32_t m = 0; for (int n = 0; n < NSUB; n++) if ((n / NB) ^ (gate(n % NB) < 0)) m |= 1u << n; return m; }();
      constexpr uint32_t LIM2 = X_LIM * 0x10001u;
      cluster_wait();
      auto conv = [&](uint2& v, uint32_t m) {
        const uint32_t tx = bmul2(v.x, xsc), ty = bmul2(v.y, xsc), ux = tx & NAN2, uy = ty & NAN2;
        v = make_uint2(ux * 7 + tx, uy * 7 + ty);
        return __vimax3_u16x2(m, ux, uy);
      };
      uint32_t so[6] = {};
      auto planes = [&](const uint2* h, uint32_t m, uint32_t a, bool on) {
        constexpr uint32_t NB2 = h2const(-B2), NA2 = h2const(-A2);
        const uint2 e1 = fma4(NB2, h[2], h[4]), e2 = fma4(NA2, h[2], h[4]);
        store_v(a + so[4], fma4(NA2, fma4(NB2, h[0], h[2]), e1), on);
        const uint2 o1 = fma4(NB2, h[1], h[3]), o2 = fma4(NA2, h[1], h[3]);
        store_v(a + so[5], fma4(NA2, o1, fma4(NB2, h[3], h[5])), on);
        uint2 v = fma4(h2const(PA), o1, e1);
        if (m != LIM2) v.x = NAN2;
        store_v(a + so[0], v, on);
        store_v(a + so[1], fma4(h2const(-PA), o1, e1), on);
        store_v(a + so[2], fma4(h2const(PB), o2, e2), on);
        store_v(a + so[3], fma4(h2const(-PB), o2, e2), on);
      };
      int r = bid, n = 0;
      uint32_t par = 0;
#pragma unroll 1
      for (int left = nitem * NSUB; left > 0; left--) {
        const int nb = n >= NB ? n - NB : n;
        uint2 d[10];
        mbar_wait(xbar, par);
#pragma unroll
        for (int i = 0; i < 6; i++) d[i] = xrow(0, i);
#pragma unroll
        for (int p = 0; p < 6; p++) so[p] = c_slots.off[n][p];
        const uint32_t gpar = (gate_par >> n) & 1;
        if (++n == NSUB) { n = 0; r += nblk; }
        const int fc = n * 16, fx = halo_x(r) + w * 8, fy = halo_y(r);
#pragma unroll
        for (int j = 0; j < 3; j++) {
          const bool on = j < 2 || in_row;
#pragma unroll
          for (int i = 6; i < 10; i++) d[i] = xrow(j, i);
          const bool xok = j < 2 && mbar_test(xbar + 8 * (j + 1), par);
          sched_barrier();
          const uint32_t m45 = conv(d[5], conv(d[4], LIM2));
          const uint32_t ma = conv(d[3], conv(d[1], conv(d[0], conv(d[2], m45))));
          if (j == 0) mbar_wait(sb + BAR_GATE + 8 * nb, gpar);
          planes(d, ma, vl + j * 384, on);
          sched_barrier();
          const uint32_t mb = conv(d[9], conv(d[7], conv(d[6], conv(d[8], m45))));
          if (left > 1) tma_box_warp(xbox + j * XBOX, j < 2 ? &tmX : tm2, xbar + 8 * j, (j < 2 ? XBOX : bytes2) | (mb & 0x8000u), fc, fx + j * 24, fy);
          uint2 h[6];
#pragma unroll
          for (int i = 0; i < 6; i++) h[i] = d[4 + i];
          if (j < 2) {
            mbar_wait(xbar + 8 * (j + 1), par, xok);
#pragma unroll
            for (int i = 0; i < 6; i++) d[i] = xrow(j + 1, i);
          }
          sched_barrier();
          planes(h, mb, vl + j * 384 + VPIECE, on);
          sched_barrier();
        }
        fence_async();
        asm volatile("{\n.reg .pred p;\nelect.sync _|p, 0xffffffff;\n@p mbarrier.arrive.shared::cta.b64 _, [%0];\n}\n" ::"r"(sb + BAR_VFULL + 8 * nb) : "memory");
        par ^= 1;
      }
    }
  }
}

constexpr uint64_t make_desc(uint32_t off, uint32_t lbo, uint32_t sbo) {
  return (uint64_t)((SMEM_BASE + off) >> 4) | ((uint64_t)(lbo >> 4) << 16) | ((uint64_t)(sbo >> 4) << 32);
}

typedef CUresult (*EncodeFn)(CUtensorMap*, CUtensorMapDataType, cuuint32_t, void*, const cuuint64_t*, const cuuint64_t*,
                             const cuuint32_t*, const cuuint32_t*, CUtensorMapInterleave, CUtensorMapSwizzle,
                             CUtensorMapL2promotion, CUtensorMapFloatOOBfill);

}

extern "C" void kernel_launch(void* const* d_in, const int* in_sizes, int n_in, void* d_out, int out_size) {
  static EncodeFn enc = nullptr;
  static int nblk = 0;
  static uint4* ubuf;
  static uint32_t* arrived;
  if (!enc) {
    cudaGetSymbolAddress((void**)&ubuf, g_U);
    cudaGetSymbolAddress((void**)&arrived, g_arrived);
    cudaDriverEntryPointQueryResult qr;
    cudaGetDriverEntryPoint("cuTensorMapEncodeTiled", (void**)&enc, cudaEnableDefault, &qr);
    cudaFuncSetAttribute(conv_kernel, cudaFuncAttributeMaxDynamicSharedMemorySize, SMEM_BYTES);
    int dev;
    cudaGetDevice(&dev);
    cudaDeviceGetAttribute(&nblk, cudaDevAttrMultiProcessorCount, dev);
  }
  CUtensorMap tmX, tmH, tmP;
  const cuuint64_t dims[3] = {CH, IMG, IMG};
  const cuuint64_t strides[2] = {CH * 2, (cuuint64_t)CH * 2 * IMG};
  const cuuint32_t es[3] = {1, 1, 1};
  const cuuint32_t boxX[3] = {16, 8, 10}, boxH[3] = {16, 2, 10}, boxP[3] = {8, PF_X, 2};
  enc(&tmH, CU_TENSOR_MAP_DATA_TYPE_BFLOAT16, 3, d_in[0], dims, strides, boxH, es, CU_TENSOR_MAP_INTERLEAVE_NONE,
      CU_TENSOR_MAP_SWIZZLE_NONE, CU_TENSOR_MAP_L2_PROMOTION_L2_64B, CU_TENSOR_MAP_FLOAT_OOB_FILL_NONE);
  enc(&tmP, CU_TENSOR_MAP_DATA_TYPE_BFLOAT16, 3, d_in[0], dims, strides, boxP, es, CU_TENSOR_MAP_INTERLEAVE_NONE,
      CU_TENSOR_MAP_SWIZZLE_NONE, CU_TENSOR_MAP_L2_PROMOTION_L2_128B, CU_TENSOR_MAP_FLOAT_OOB_FILL_NONE);
  enc(&tmX, CU_TENSOR_MAP_DATA_TYPE_BFLOAT16, 3, d_in[0], dims, strides, boxX, es, CU_TENSOR_MAP_INTERLEAVE_NONE,
      CU_TENSOR_MAP_SWIZZLE_32B, CU_TENSOR_MAP_L2_PROMOTION_L2_64B, CU_TENSOR_MAP_FLOAT_OOB_FILL_NONE);
  Descs desc = {};
  for (int i = 0; i < 6; i++) { desc.a[0][i] = make_desc(OFF_V, VROW, 128); desc.a[1][i] = make_desc(OFF_V + VPIECE, VROW, 128); }
  for (int i = 0; i < 22; i++) desc.b[i] = make_desc(OFF_U, 128, 256);
  conv_kernel<<<nblk, 384, SMEM_BYTES>>>(tmX, tmH, tmP, (const __nv_bfloat16*)d_in[0], (const __nv_bfloat16*)d_in[1], (__nv_bfloat16*)d_out, ubuf, arrived, nblk,
                                         NREG % nblk ? NREG % nblk : nblk, (NREG + nblk - 1) / nblk, desc);
}
```

```cpp
#include <cuda_runtime.h>
#include <cuda_bf16.h>
#include <cuda.h>
#include <stdint.h>

namespace {

constexpr int IMG = 512, CH = 192;
constexpr float PA = 0.6875f, PB = 1.5f;
constexpr float A2 = PA * PA, B2 = PB * PB, DD = B2 - A2;

constexpr int NSTEP = 72, NSUB = 12;
__host__ __device__ constexpr int sched(int i) {
  constexpr int t[NSTEP] = {
      0x00, 0x10, 0x20, 0x01, 0x11, 0x21, 0x02, 0x12, 0x22, 0x03, 0x13, 0x23, 0x30, 0x31, 0x32, 0x33, 0x24, 0x34,
      0x04, 0x14, 0x25, 0x35, 0x05, 0x15, 0x26, 0x36, 0x06, 0x16, 0x27, 0x37, 0x07, 0x17, 0x28, 0x38, 0x08, 0x18,
      0x29, 0x39, 0x09, 0x19, 0x2a, 0x3a, 0x0a, 0x1a, 0x2b, 0x3b, 0x1b, 0x0b, 0x40, 0x4b, 0x50, 0x41, 0x51, 0x4a,
      0x49, 0x48, 0x47, 0x42, 0x52, 0x46, 0x45, 0x5b, 0x44, 0x43, 0x5a, 0x53, 0x59, 0x58, 0x57, 0x56, 0x54, 0x55};
  return t[i];
}
__host__ __device__ constexpr int step_p(int i) { return sched(i) >> 4; }
__host__ __device__ constexpr int step_n(int i) { return sched(i) & 15; }
__host__ __device__ constexpr int step_acc(int i) { return step_p(i) < 4 ? step_p(i) : step_p(i) - 2; }
__host__ __device__ constexpr int first_on(int acc) {
  for (int i = 0; i < NSTEP; i++)
    if (step_acc(i) == acc) return i;
  return -1;
}
__host__ __device__ constexpr int last_on(int acc) {
  for (int i = NSTEP - 1; i >= 0; i--)
    if (step_acc(i) == acc) return i;
  return -1;
}
__host__ __device__ constexpr int find_step(int p, int n) {
  for (int i = 0; i < NSTEP; i++)
    if (sched(i) == p * 16 + n) return i;
  return -1;
}
__host__ __device__ constexpr int first_use(int n) {
  for (int i = 0; i < NSTEP; i++)
    if (step_n(i) == n) return i;
  return -1;
}
constexpr int NHEAD = first_on(3) / 3 * 4;
__host__ __device__ constexpr int head(int i) { return i < NHEAD ? find_step(i % 4, i / 4) : i; }
constexpr float S1 = 1.f / PA, S2 = 1.f / (2.f * A2), S3 = -A2 / (2.f * DD), S4 = -1.f / (PB * DD);
constexpr int PIV = find_step(3, NSUB - 1);
static_assert(find_step(2, NSUB - 1) == PIV - 1 && last_on(1) == PIV + 1 && last_on(0) == PIV + 2 && PIV + 3 == 4 * NSUB &&
              step_p(PIV + 3) == 4 && step_p(PIV + 4) == 4 && step_p(PIV + 5) == 5, "basis change");

constexpr int NV = 32, NB = 6;
__host__ __device__ constexpr int vslot(int p, int n) {
  constexpr int t[6][NSUB] = {
      {31, 19, 25, 18, 19, 27, 21, 4, 24, 26, 3, 26}, {28, 23, 24, 22, 17, 24, 28, 3, 25, 27, 0, 28}, {27, 17, 14,
      20, 23, 22, 20, 31, 0, 28, 1, 2}, {26, 21, 15, 16, 31, 18, 23, 26, 23, 31, 4, 31}, {7, 6, 8, 10, 12, 14, 15,
      17, 19, 21, 23, 27}, {30, 29, 9, 11, 13, 5, 16, 18, 20, 22, 24, 25}};
  return t[p][n];
}
__host__ __device__ constexpr int gate(int n) {
  constexpr int t[NSUB] = {-20, -14, -8, -2, 5, 11, 16, 21, 25, 29, 34, 39};
  return t[n];
}
__host__ __device__ constexpr int gate_of(int i) {
  for (int n = 0; n < NSUB; n++)
    if ((gate(n) + NSTEP) % NSTEP == i) return n;
  return -1;
}
__host__ __device__ constexpr int head_gate_of(int i) {
  for (int n = 0; n < NSUB; n++) {
    int m = -1;
    for (int j = 0; j < NHEAD; j++)
      if (head(j) <= gate(n)) m = j;
    if (gate(n) < NHEAD && m == i) return n;
  }
  return -1;
}
__host__ __device__ constexpr bool gates_ok() {
  int early = 0;
  for (int i = 0; i < NHEAD; i++) early += (gate_of(i) >= 0) - (head_gate_of(i) >= 0) + (head(i) >= NHEAD);
  if (early) return false;
  for (int n = 0; n < NSUB; n++) {
    for (int p = 0; p < 6; p++)
      for (int d = 1; d <= NSUB; d++)
        for (int q = 0; q < 6; q++) {
          const int m = (n - d + NSUB) % NSUB;
          if (vslot(q, m) == vslot(p, n) && (find_step(q, m) - (n - d < 0 ? NSTEP : 0) > gate(n) || (m == n && p != q))) return false;
        }
    if (n > 0 && (gate(n) <= gate(n - 1) || first_use(n) <= first_use(n - 1))) return false;
    if (gate(n) >= first_use(n)) return false;
    if (gate((n + NB) % NSUB) + (n >= NB ? NSTEP : 0) < first_use(n)) return false;
  }
  return gate(0) + NSTEP > gate(NSUB - 1) && gate(NB) >= 0;
}
static_assert(gates_ok(), "gates");

constexpr int UTILE = CH * 16 * 2;
constexpr int USLAB = 3 * UTILE;
constexpr int NU = 4;
constexpr int VROW = 66 * 16;
constexpr int VPIECE = 2 * VROW;
constexpr int VSLOT = 2 * VPIECE;
constexpr int XBOX = 10 * 8 * 32;
constexpr int XHBOX = 10 * 2 * 32;
constexpr int UX_FIRST = 52, UX_COUNT = 8, UX_GATE = UX_FIRST - NU - 1;
__host__ __device__ constexpr bool uextra(int i) {
  const int d = (i - UX_FIRST + NSTEP) % NSTEP;
  return d % (NU + 1) == 0 && d / (NU + 1) < UX_COUNT;
}
__host__ __device__ constexpr int uindex(int i) {
  int c = 0;
  for (int j = 0; j < i; j++) c += uextra(j) == uextra(i);
  return c;
}
__host__ __device__ constexpr int uslot(int i) { return uextra(i) ? NU : uindex(i) % NU; }
__host__ __device__ constexpr int uuse(int i) { return uextra(i) ? uindex(i) : uindex(i) / NU; }
__host__ __device__ constexpr int utrigger(int j) {
  if (j == UX_FIRST) return UX_GATE;
  int i = j - 1;
  while (uslot((i + NSTEP) % NSTEP) != uslot(j)) i--;
  return i;
}
template <int I> constexpr int USLOT = uslot(I);
template <int I> constexpr int UUSE = uuse(I);
__host__ __device__ constexpr bool uring_ok() {
  for (int n = 0; n < NSUB; n++)
    for (int p = 0; p < 6; p++)
      if (vslot(p, n) * VSLOT < USLAB &&
          (find_step(p, n) > UX_GATE || gate(n) < UX_FIRST + (NU + 1) * (UX_COUNT - 1) - NSTEP))
        return false;
  return UX_COUNT % 2 == 0 && (NSTEP - UX_COUNT) % (2 * NU) == 0;
}
static_assert(uring_ok(), "U ring");

constexpr int OFF_X = 0;
constexpr int OFF_SINK = OFF_X + 8 * XBOX + XHBOX;
constexpr int OFF_U = OFF_SINK + 768;
constexpr int OFF_V = OFF_U + NU * USLAB;
constexpr int OFF_BAR = OFF_V + NV * VSLOT;
constexpr int BAR_UFULL = OFF_BAR;
constexpr int BAR_UEMPTY = BAR_UFULL + 8 * (NU + 1);
constexpr int BAR_XFULL = BAR_UEMPTY + 8 * (NU + 1);
constexpr int BAR_VFULL = BAR_XFULL + 8 * 9;
constexpr int BAR_GATE = BAR_VFULL + 8 * NB;
constexpr int BAR_SINK = BAR_GATE + 8 * NB;
constexpr int OFF_OSC = BAR_SINK + 8;
constexpr int NBAR = (OFF_OSC - OFF_BAR) / 8;
constexpr int SMEM_BYTES = OFF_OSC + 8;
constexpr uint32_t SMEM_BASE = 1024;
static_assert(SMEM_BYTES <= 232448, "smem");

constexpr int NREG = 512;

__device__ __align__(128) uint4 g_U[NSTEP * USLAB / 16];
__device__ uint32_t g_arrived[4 * 32];

__device__ __forceinline__ uint32_t smem_u32(const void* p) { return (uint32_t)__cvta_generic_to_shared(p); }
__device__ __forceinline__ void mbar_init(uint32_t a, int c) {
  asm volatile("mbarrier.init.shared::cta.b64 [%0], %1;" ::"r"(a), "r"(c) : "memory");
}
__device__ __forceinline__ void mbar_arrive(uint32_t a) {
  asm volatile("mbarrier.arrive.shared::cta.b64 _, [%0];" ::"r"(a) : "memory");
}
__device__ __forceinline__ void mbar_wait(uint32_t a, uint32_t parity, uint32_t skip = 0) {
  asm volatile(
      "{\n"
      ".reg .pred p;\n"
      ".reg .u32 n;\n"
      "setp.ne.u32 p, %2, 0;\n"
      "@p bra.uni LAB_DONE;\n"
      "mov.u32 n, 0;\n"
      "LAB_WAIT:\n"
      "mbarrier.try_wait.parity.shared::cta.b64 p, [%0], %1;\n"
      "@p bra.uni LAB_DONE;\n"
      "add.u32 n, n, 1;\n"
      "setp.lt.u32 p, n, 4000000;\n"
      "@p bra.uni LAB_WAIT;\n"
      "trap;\n"
      "LAB_DONE:\n"
      "}\n" ::"r"(a), "r"(parity), "r"(skip) : "memory");
}
__device__ __forceinline__ void mbar_wait_short(uint32_t a, uint32_t parity) {
  asm volatile("{\n.reg .pred p;\nLAB_WAIT:\nmbarrier.try_wait.parity.shared::cta.b64 p, [%0], %1;\n@!p bra.uni LAB_WAIT;\n}\n" ::"r"(a),
               "r"(parity) : "memory");
}
__device__ __forceinline__ bool mbar_test(uint32_t a, uint32_t parity) {
  uint32_t ok;
  asm volatile("{\n.reg .pred p;\nmbarrier.test_wait.parity.shared::cta.b64 p, [%1], %2;\nselp.u32 %0, 1, 0, p;\n}\n"
               : "=r"(ok) : "r"(a), "r"(parity) : "memory");
  return ok;
}
__device__ __forceinline__ void fence_async() { asm volatile("fence.proxy.async.shared::cta;" ::: "memory"); }
__device__ __forceinline__ void tma_box_warp(uint32_t dst, const CUtensorMap* tm, uint32_t bar, uint32_t bytes, int c, int x, int y) {
  asm volatile(
      "{\n.reg .pred p;\nelect.sync _|p, 0xffffffff;\n"
      "@p mbarrier.arrive.expect_tx.shared::cta.b64 _, [%2], %6;\n"
      "@p cp.async.bulk.tensor.3d.shared::cluster.global.mbarrier::complete_tx::bytes [%0], [%1, {%3, %4, %5}], [%2];\n}\n" ::"r"(dst),
      "l"(tm), "r"(bar), "r"(c), "r"(x), "r"(y), "r"(bytes) : "memory");
}
__device__ __forceinline__ void load_u_warp(uint32_t dst, const void* src, uint32_t bar) {
  asm volatile("{\n.reg .pred p;\nelect.sync _|p, 0xffffffff;\n"
               "@p mbarrier.arrive.expect_tx.shared::cta.b64 _, [%2], %3;\n"
               "@p cp.async.bulk.shared::cluster.global.mbarrier::complete_tx::bytes [%0], [%1], %3, [%2];\n}\n" ::"r"(dst),
               "l"(src), "r"(bar), "n"(USLAB) : "memory");
}
__device__ __forceinline__ void refill_u(uint32_t ebar, uint32_t parity, uint32_t on, uint32_t dst, const void* src) {
  asm volatile(
      "{\n.reg .pred p;\n.reg .u32 n;\n"
      "mov.u32 n, 0;\n"
      "LAB_WAIT:\n"
      "mbarrier.try_wait.parity.shared::cta.b64 p, [%0], %1;\n"
      "@p bra.uni LAB_DONE;\n"
      "add.u32 n, n, 1;\nsetp.lt.u32 p, n, 4000000;\n"
      "@p bra.uni LAB_WAIT;\n"
      "trap;\n"
      "LAB_DONE:\n"
      "setp.eq.u32 p, %2, 0;\n"
      "@p bra.uni LAB_OUT;\n"
      "elect.sync _|p, 0xffffffff;\n"
      "@p mbarrier.arrive.expect_tx.shared::cta.b64 _, [%5], %6;\n"
      "@p cp.async.bulk.shared::cluster.global.mbarrier::complete_tx::bytes [%3], [%4], %6, [%5];\n"
      "LAB_OUT:\n}\n" ::"r"(ebar), "r"(parity), "r"(on), "r"(dst), "l"(src), "r"(ebar - (BAR_UEMPTY - BAR_UFULL)), "n"(USLAB) : "memory");
}
__device__ __forceinline__ uint2 lds64(uint32_t a) {
  uint2 v;
  asm volatile("ld.shared.v2.u32 {%0,%1}, [%2];" : "=r"(v.x), "=r"(v.y) : "r"(a) : "memory");
  return v;
}
__device__ __forceinline__ uint32_t lds32(uint32_t a) {
  uint32_t v;
  asm volatile("ld.shared.u32 %0, [%1];" : "=r"(v) : "r"(a) : "memory");
  return v;
}
__device__ __forceinline__ void store_v(uint32_t a, uint2 v, bool on) {
  v.x &= 0xFFFCFFFCu; v.y &= 0xFFFCFFFCu;
  if (on) asm volatile("st.shared.v2.u32 [%0], {%1,%2};" ::"r"(a), "r"(v.x), "r"(v.y) : "memory");
}
__device__ __forceinline__ void sched_barrier() { asm volatile("pmevent 0;" ::: "memory"); }
__device__ __forceinline__ void spin_cycles(uint32_t n) {
  asm volatile(
      "{\n.reg .pred p;\n.reg .u32 t0, t;\n"
      "mov.u32 t0, %%clock;\n"
      "LAB_SPIN:\n"
      "nanosleep.u32 50;\n"
      "mov.u32 t, %%clock;\nsub.u32 t, t, t0;\nsetp.lt.u32 p, t, %0;\n"
      "@p bra.uni LAB_SPIN;\n}\n" ::"r"(n) : "memory");
}
__device__ __forceinline__ void spin_until(uint32_t t0, uint32_t n) {
  asm volatile("{\n.reg .pred p;\n.reg .u32 t;\nLAB_SPIN:\nmov.u32 t, %%clock;\nsub.u32 t, t, %0;\nsetp.lt.u32 p, t, %1;\n@p bra.uni LAB_SPIN;\n}\n" ::"r"(t0),
               "r"(n) : "memory");
}
__device__ __forceinline__ uint32_t now() {
  uint32_t t;
  asm volatile("mov.u32 %0, %%clock;" : "=r"(t)::"memory");
  return t;
}
__device__ __forceinline__ uint32_t stage_enter(uint32_t* ctr, int lane, uint32_t inc) {
  uint32_t old;
  asm volatile("{\n.reg .pred p;\nsetp.eq.u32 p, %2, 0;\nld.relaxed.gpu.global.u32 %0, [%1];\n@p red.relaxed.gpu.global.add.u32 [%1], %3;\n}"
               : "=r"(old) : "l"(ctr), "r"(lane), "r"(inc) : "memory");
  return old;
}
__device__ __forceinline__ void stage_wait(const uint32_t* ctr, uint32_t old) {
  asm volatile(
      "{\n.reg .pred p;\n.reg .u32 v, i;\n"
      "mov.u32 i, 0;\n"
      "LAB_POLL:\n"
      "ld.acquire.gpu.global.u32 v, [%0];\n"
      "xor.b32 v, v, %1;\nsetp.lt.s32 p, v, 0;\n"
      "@p bra.uni LAB_OUT;\n"
      "add.u32 i, i, 1;\nsetp.lt.u32 p, i, 4000000;\n"
      "@p bra.uni LAB_POLL;\n"
      "trap;\n"
      "LAB_OUT:\n"
      "fence.proxy.async.global;\n}\n" ::"l"(ctr), "r"(old) : "memory");
}
__device__ __forceinline__ void cluster_arrive_relaxed() { asm volatile("barrier.cluster.arrive.relaxed.aligned;" ::: "memory"); }
__device__ __forceinline__ void cluster_wait() { asm volatile("barrier.cluster.wait.acquire.aligned;" ::: "memory"); }

__host__ __device__ constexpr uint32_t h2const(float v) {
  double a = v < 0 ? -v : v;
  int e = 15;
  while (a >= 2) { a /= 2; e++; }
  while (a < 1) { a *= 2; e--; }
  const uint32_t h = (v < 0 ? 0x8000u : 0u) | ((e << 10) + (uint32_t)((a - 1) * 1024 + 0.5));
  return h | h << 16;
}
__device__ __forceinline__ uint32_t hfma2(uint32_t a, uint32_t b, uint32_t c) {
  uint32_t d;
  asm("fma.rn.f16x2 %0, %1, %2, %3;" : "=r"(d) : "r"(a), "r"(b), "r"(c));
  return d;
}
__device__ __forceinline__ uint32_t bmul2(uint32_t a, uint32_t b) {
  uint32_t d;
  asm("mul.rn.bf16x2 %0, %1, %2;" : "=r"(d) : "r"(a), "r"(b));
  return d;
}
__device__ __forceinline__ uint2 fma4(uint32_t k, const uint2& a, const uint2& c) { return make_uint2(hfma2(k, a.x, c.x), hfma2(k, a.y, c.y)); }
__device__ __forceinline__ uint32_t pack_bf16(float lo, float hi) {
  uint32_t d;
  asm("cvt.rn.bf16x2.f32 %0, %1, %2;" : "=r"(d) : "f"(hi), "f"(lo));
  return d;
}
__device__ __forceinline__ uint32_t pack_f16(float lo, float hi) {
  uint32_t d;
  asm("cvt.rn.f16x2.f32 %0, %1, %2;" : "=r"(d) : "f"(hi), "f"(lo));
  return d;
}

template <int AOFF, int BOFF>
__device__ __forceinline__ void wgmma192(uint32_t (&d)[48], uint64_t da, uint64_t db, uint32_t scale_d) {
  asm volatile(
      "{\n.reg .pred p;\n.reg .b64 qa, qb;\n"
      "setp.ne.b32 p, %50, 0;\n"
      "add.s64 qa, %48, %51;\nadd.s64 qb, %49, %52;\n"
      "wgmma.mma_async.sync.aligned.m64n192k16.f16.f16.f16 "
      "{%0, %1, %2, %3, %4, %5, %6, %7, %8, %9, %10, %11, %12, %13, %14, %15, "
      "%16, %17, %18, %19, %20, %21, %22, %23, %24, %25, %26, %27, %28, %29, %30, %31, "
      "%32, %33, %34, %35, %36, %37, %38, %39, %40, %41, %42, %43, %44, %45, %46, %47}, "
      "qa, qb, p, 1, 1, 0, 0;\n}\n"
      : "+r"(d[0]), "+r"(d[1]), "+r"(d[2]), "+r"(d[3]), "+r"(d[4]), "+r"(d[5]), "+r"(d[6]), "+r"(d[7]), "+r"(d[8]),
        "+r"(d[9]), "+r"(d[10]), "+r"(d[11]), "+r"(d[12]), "+r"(d[13]), "+r"(d[14]), "+r"(d[15]), "+r"(d[16]),
        "+r"(d[17]), "+r"(d[18]), "+r"(d[19]), "+r"(d[20]), "+r"(d[21]), "+r"(d[22]), "+r"(d[23]), "+r"(d[24]),
        "+r"(d[25]), "+r"(d[26]), "+r"(d[27]), "+r"(d[28]), "+r"(d[29]), "+r"(d[30]), "+r"(d[31]), "+r"(d[32]),
        "+r"(d[33]), "+r"(d[34]), "+r"(d[35]), "+r"(d[36]), "+r"(d[37]), "+r"(d[38]), "+r"(d[39]), "+r"(d[40]),
        "+r"(d[41]), "+r"(d[42]), "+r"(d[43]), "+r"(d[44]), "+r"(d[45]), "+r"(d[46]), "+r"(d[47])
      : "l"(da), "l"(db), "r"(scale_d), "n"(AOFF >> 4), "n"(BOFF >> 4));
}
__device__ __forceinline__ void wg_fence() { asm volatile("wgmma.fence.sync.aligned;" ::: "memory"); }
__device__ __forceinline__ void wg_commit() { asm volatile("wgmma.commit_group.sync.aligned;" ::: "memory"); }
template <int N>
__device__ __forceinline__ void wg_wait() { asm volatile("wgmma.wait_group.sync.aligned %0;" ::"n"(N) : "memory"); }
__device__ __forceinline__ void reg_fence(uint32_t (&d)[48]) {
#pragma unroll
  for (int i = 0; i < 48; i++) asm volatile("" : "+r"(d[i])::"memory");
}

constexpr uint32_t X_EXP = 17;
constexpr uint32_t X_LIM = ((15 + 8) << 7) - 1;
constexpr uint32_t U_LIM = ((15 + 6) << 10) - 1;
constexpr uint32_t Y_MIN = 0x3C00, Y_INF = 0x7C00;
constexpr uint32_t NAN2 = 0x7FFF7FFFu;
using Sample = uint4;
__device__ __forceinline__ uint4 ldg128(const uint4* p) {
  uint4 v;
  asm volatile("ld.global.v4.u32 {%0,%1,%2,%3}, [%4];" : "=r"(v.x), "=r"(v.y), "=r"(v.z), "=r"(v.w) : "l"(p));
  return v;
}
__device__ __forceinline__ Sample sample_w(const __nv_bfloat16* w, int lane) {
  const int q = lane >> 3;
  return ldg128((const uint4*)(w + ((q == 0 ? 1 : q == 1 ? 3 : 4) * CH + 47 * q) * CH + 64 * (q % 3)) + (lane & 7));
}
__device__ __forceinline__ Sample sample_x(const __nv_bfloat16* x, int r, int lane) {
  return ldg128((const uint4*)(x + (size_t)(((r >> 3) * 8 + 1 + lane % 6) * IMG + (r & 7) * 64 + 2 * lane) * CH) + lane % 24);
}
__device__ __forceinline__ uint32_t sample_exp(const Sample& s) {
  const uint32_t m = __vmaxu2(__vimax3_u16x2(s.x & NAN2, s.y & NAN2, s.z & NAN2), s.w & NAN2);
  return __reduce_max_sync(0xffffffffu, max(m & 0xFFFFu, m >> 16)) >> 7;
}

constexpr int NP = 16, NTASK = NSUB * 36, NROUND = (NTASK + 8 * NP - 1) / (8 * NP), NSTAGE = 3;
__host__ __device__ constexpr int stage_end(int k) { return k == 0 ? 1 : k == 1 ? 3 : 2 * NROUND; }
__host__ __device__ constexpr int stage_first(int k) {
  for (int i = 0; i < NSTEP; i++)
    if (step_p(head(i)) / 4 * NROUND * 8 * NP + (step_n(head(i)) + 1) * 36 > stage_end(k - 1) * 8 * NP) return i;
  return -1;
}
static_assert(utrigger(stage_first(1)) >= 0 && stage_first(2) > stage_first(1), "stages");
struct Task {
  uint32_t n, s, kh, k;
  __device__ __forceinline__ Task(uint32_t t, int lane) {
    const uint32_t sub = t % 36;
    n = t / 36, s = sub / 12, kh = (sub / 6) & 1, k = sub % 6 * 32 + lane;
  }
};
constexpr int WTASK = 24 * 64;
__device__ __forceinline__ void prep_load(uint32_t dst, const __nv_bfloat16* __restrict__ w, uint32_t t, int lane) {
  const Task q(min(t, NTASK - 1), 0);
  w += ((q.s * 24 + 2 * q.n + q.kh) * 8 + (lane >> 2)) * CH + q.k + (lane & 3) * 8;
#pragma unroll
  for (int r = 0; r < 3; r++)
    asm volatile("cp.async.cg.shared.global [%0], [%1], 16;" ::"r"(dst + r * 512 + lane * 16), "l"(w + r * 3 * CH * CH) : "memory");
}
__device__ __forceinline__ void prep_store(const float (&g)[3][8], uint4* u, uint32_t t, bool h, int lane) {
  const Task q(t, lane);
  const uint32_t n = q.n, s = q.s, kh = q.kh, k = q.k;
  const uint32_t jn = (k >> 5) * 4 + ((k >> 1) & 3), row = ((k >> 3) & 3) * 2 + (k & 1);
  u += (((h ? 4 * NSUB : 0) + n) * USLAB + s * UTILE + jn * 256 + kh * 128 + row * 16) >> 4;
  constexpr float nA = -1.f / (2.f * A2 * DD), nB = 1.f / (2.f * B2 * DD);
  constexpr float f0 = nA / S1, f1 = nA / S2, f2 = nB / S3, f3 = nB / S4, f4 = 1.f / (A2 * B2);
  const float co[4][3] = {{h ? f4 : f0, h ? 0.f : PA * f0, h ? 0.f : A2 * f0},
                          {h ? 0.f : f1, h ? 0.f : -PA * f1, h ? 1.f : A2 * f1},
                          {f2, PB * f2, B2 * f2},
                          {f3, -PB * f3, B2 * f3}};
#pragma unroll
  for (int p = 0; p < 4; p++) {
    if (p == 2 && h) break;
    uint32_t o[4];
#pragma unroll
    for (int e = 0; e < 4; e++) {
      float v[2];
#pragma unroll
      for (int q = 0; q < 2; q++) v[q] = co[p][0] * g[0][2 * e + q] + co[p][1] * g[1][2 * e + q] + co[p][2] * g[2][2 * e + q];
      const uint32_t b = pack_bf16(v[0], v[1]);
      o[e] = pack_f16(__uint_as_float(b << 16), __uint_as_float(b & 0xFFFF0000u));
    }
    constexpr uint32_t lim = U_LIM * 0x10001u;
    if (__vimax3_u16x2(__vimax3_u16x2(lim, o[0] & NAN2, o[1] & NAN2), o[2] & NAN2, o[3] & NAN2) != lim) o[0] = NAN2;
    u[p * NSUB * USLAB / 16] = make_uint4(o[0], o[1], o[2], o[3]);
  }
}

constexpr int ROWB = IMG * CH * 2;

__device__ __forceinline__ int region_px(int r) { return (r >> 3) * 8 * IMG + (r & 7) * 64; }
__device__ __forceinline__ int halo_x(int r) { return (r & 7) * 64 - 1; }
__device__ __forceinline__ int halo_y(int r) { return (r >> 3) * 8 - 1; }

__device__ __noinline__ void direct_patch(const __nv_bfloat16* __restrict__ x, const __nv_bfloat16* __restrict__ w,
                                          __nv_bfloat16* __restrict__ out, int y0, int x0, int lane) {
  const int g = lane >> 2, t = lane & 3;
#pragma unroll 1
  for (int k0 = 0; k0 < CH; k0 += 48) {
    float acc[4][6][4] = {};
#pragma unroll 1
    for (int rs = 0; rs < 9; rs++) {
      const int iy = y0 + rs / 3 - 1, ix = x0 + rs % 3 - 1 + g;
#pragma unroll 2
      for (int c = 4 * t; c < CH; c += 16) {
        uint32_t b[6][2];
#pragma unroll
        for (int m = 0; m < 6; m++) {
          const uint32_t* p = (const uint32_t*)(w + (rs * CH + c + (m & 1) * 2) * CH + k0 + (m >> 1) * 16 + 2 * g);
          const uint32_t lo = p[0], hi = p[CH / 2];
          b[m & 6][m & 1] = __byte_perm(lo, hi, 0x5410);
          b[m | 1][m & 1] = __byte_perm(lo, hi, 0x7632);
        }
#pragma unroll
        for (int y = 0; y < 4; y++) {
          uint2 a[2];
#pragma unroll
          for (int h = 0; h < 2; h++)
            a[h] = (unsigned)(iy + y) < IMG && (unsigned)(ix + 8 * h) < IMG ? *(const uint2*)(x + ((iy + y) * IMG + ix + 8 * h) * CH + c)
                                                                           : make_uint2(0, 0);
#pragma unroll
          for (int m = 0; m < 6; m++)
            asm("mma.sync.aligned.m16n8k16.row.col.f32.bf16.bf16.f32 {%0,%1,%2,%3}, {%4,%5,%6,%7}, {%8,%9}, {%0,%1,%2,%3};"
                : "+f"(acc[y][m][0]), "+f"(acc[y][m][1]), "+f"(acc[y][m][2]), "+f"(acc[y][m][3])
                : "r"(a[0].x), "r"(a[1].x), "r"(a[0].y), "r"(a[1].y), "r"(b[m][0]), "r"(b[m][1]));
        }
      }
    }
#pragma unroll
    for (int y = 0; y < 4; y++)
#pragma unroll
      for (int m = 0; m < 6; m += 2)
#pragma unroll
        for (int h = 0; h < 2; h++)
          *(uint2*)(out + ((y0 + y) * IMG + x0 + g + 8 * h) * CH + k0 + m * 8 + 4 * t) =
              make_uint2(pack_bf16(acc[y][m][2 * h], acc[y][m + 1][2 * h]), pack_bf16(acc[y][m][2 * h + 1], acc[y][m + 1][2 * h + 1]));
  }
}

struct Descs { uint64_t a[2][6], b[22]; };
__host__ __device__ constexpr int slot_use(int i) {
  int c = 0;
  for (int j = 0; j < i; j++) c += vslot(step_p(j), step_n(j)) == vslot(step_p(i), step_n(i));
  return c;
}

__host__ __device__ constexpr int out_time(int q) {
  constexpr int t[24] = {
      49, 50, 51, 52, 54, 55, 56, 57, 59, 60, 61, 63, 64, 65, 66, 68, 69, 70, 72, 74, 76, 78, 80, 82};
  return t[q];
}
__host__ __device__ constexpr int out_at(int t) {
  for (int q = 0; q < 24; q++)
    if (out_time(q) % NSTEP == t) return q;
  return -1;
}
__host__ __device__ constexpr bool out_ok() {
  for (int q = 0; q < 24; q++)
    if (out_time(q) <= last_on(q / 6) || out_time(q) < PIV + (q < 12 ? 4 : 6) || out_time(q) >= first_on(q / 6) + NSTEP ||
        (q && out_time(q) <= out_time(q - 1)))
      return false;
  return true;
}
static_assert(out_ok(), "output plan");
constexpr int OUT_END = out_time(23) + 1 - NSTEP;

struct Consumer {
  uint32_t c1[48], c2[48], c3[48], c4[48];
  const uint64_t *descA, *descB;
  static constexpr uint32_t sb = SMEM_BASE;
  uint8_t* pout;
  int bid, nblk, nlong;
  uint32_t done;
  uint32_t osc, ymax, redo;
  bool lead, ok, odd;

  uint32_t one;
  __device__ __forceinline__ bool always() {
    uint32_t v = one;
    asm volatile("" : "+r"(v));
    return v != 0;
  }
  __device__ __forceinline__ void axpy(uint32_t (&a)[48], uint32_t k, uint32_t (&b)[48]) {
    if (always()) {
      reg_fence(a); reg_fence(b);
#pragma unroll
      for (int i = 0; i < 48; i++) {
        a[i] = hfma2(k, b[i], a[i]);
        if (i % 12 == 11) {
          asm volatile("" : "+r"(a[i])::"memory");
          sched_barrier();
        }
      }
      reg_fence(a);
    }
  }
  uint32_t pa[4], pb[4], px[4];
  __device__ __forceinline__ uint32_t to_bf16(uint32_t h) {
    float lo, hi;
    asm("{\n.reg .b16 l, h;\n.reg .b32 m;\nmov.b32 {l, h}, %3;\ncvt.f32.f16 %0, l;\ncvt.f32.f16 %1, h;\n"
        "abs.f16x2 m, %3;\nmax.NaN.f16x2 %2, m, %2;\n}\n" : "=f"(lo), "=f"(hi), "+r"(ymax) : "r"(h));
    return bmul2(pack_bf16(lo, hi), osc);
  }
  template <int Q, int EXTRA>
  __device__ __forceinline__ void stg(const uint32_t (&v)[4]) {
    constexpr int y = Q < 6 ? 1 : Q < 12 ? 2 : Q < 18 ? 0 : 3;
    asm volatile("st.global.cs.v4.u32 [%0+%5], {%1,%2,%3,%4};" ::"l"(pout), "r"(v[0]), "r"(v[1]), "r"(v[2]), "r"(v[3]),
                 "n"(y * ROWB + (Q / 3) % 2 * 8 * (CH * 2) + Q % 3 * 128 + EXTRA) : "memory");
  }
  template <int Q, bool YIELD>
  __device__ __forceinline__ void convert(uint32_t (&a)[4], uint32_t (&b)[4], uint32_t (&send)[4]) {
    if constexpr (Q >= 0) {
      const uint32_t(&d)[48] = Q < 6 ? c1 : Q < 12 ? c2 : Q < 18 ? c3 : c4;
      constexpr int o = 16 * (Q % 3) + (Q / 3) % 2;
#pragma unroll
      for (int e = 0; e < 4; e++) {
        if (YIELD && e % 2 == 0) sched_barrier();
        a[e] = to_bf16(d[o + 2 * e]);
        b[e] = to_bf16(d[o + 8 + 2 * e]);
        send[e] = odd ? a[e] : b[e];
      }
    }
  }
  template <int QW, int QR, bool STEP>
  __device__ __forceinline__ void output() {
    uint32_t u[4], v[4], a[4], b[4], send[4];
    if constexpr (!STEP) convert<QR, false>(a, b, send);
    sched_barrier();
#pragma unroll
    for (int e = 0; e < 4; e++) {
      u[e] = odd ? px[e] : pa[e];
      v[e] = odd ? pb[e] : px[e];
    }
    if constexpr (STEP) {
      convert<QR, true>(a, b, send);
      asm volatile("{\n.reg .pred p;\nsetp.ne.u32 p, %0, 0;\n@p pmevent 0;\n}" ::"r"((uint32_t)ok) : "memory");
      sched_barrier();
    }
    if constexpr (QW >= 0 && STEP) { stg<QW, 0>(u); stg<QW, CH * 2>(v); }
    if constexpr (QR >= 0) {
#pragma unroll
      for (int e = 0; e < 4; e++) px[e] = __shfl_xor_sync(0xffffffffu, send[e], 4), pa[e] = a[e], pb[e] = b[e];
    }
    if constexpr (QW >= 0 && !STEP) { stg<QW, 0>(u); stg<QW, CH * 2>(v); }
    sched_barrier();
  }
  __device__ __forceinline__ void range_check() {
    const uint32_t m = __reduce_max_sync(0xffffffffu, max(ymax & 0xFFFFu, ymax >> 16));
    redo |= (uint32_t)(m - Y_MIN >= Y_INF - Y_MIN) << done;
    ymax = 0;
  }
  template <int T, int Q0, int Q1, int Q = Q0>
  __device__ __forceinline__ void flush() {
    if constexpr (Q <= Q1) {
      constexpr int QW = Q > Q0 && out_time((Q + 23) % 24) >= T - 1 ? Q - 1 : -1, QR = Q < Q1 && out_time(Q % 24) >= T ? Q : -1;
      if constexpr (QW >= 0 || QR >= 0) output<QW, QR, false>();
      flush<T, Q0, Q1, Q + 1>();
    }
  }
  template <int I>
  __device__ __forceinline__ void hook() {
    constexpr float LP = PB * (PB - PA) / (2.f * A2), LM = PB * (PB + PA) / (2.f * A2);
    constexpr int QW = out_at((I + NSTEP - 1) % NSTEP), QR = out_at(I);
    if constexpr (QW >= 0 || QR >= 0) output<QW, QR, true>();
    if constexpr (I == 22) {
      static_assert(OUT_END < NHEAD, "pointer update");
      range_check();
      osc = lds32(sb + OFF_OSC);
      const int r = bid + done * nblk, d = region_px(r) - region_px(r - nblk);
      asm volatile("mad.wide.s32 %0, %1, 384, %0;" : "+l"(pout) : "r"(d));
    }
    if constexpr (I == NHEAD) { if (bid >= nlong && done == 0 && !(bid & 3)) spin_cycles(24500); }
    if constexpr (I == 42) { if (bid >= nlong && done == 0 && (bid & 3)) spin_cycles(28000); }
    if constexpr (I == PIV) axpy(c1, h2const(S3 * (B2 / A2) / S1), c3);
    if constexpr (I == PIV) axpy(c2, h2const(S3 * (B2 / A2) / S2), c3);
    if constexpr (I == PIV + 1) axpy(c4, h2const(-S3 / S4), c3);
    if constexpr (I == PIV + 1) axpy(c1, h2const(S4 * LP / S1), c4);
    if constexpr (I == PIV + 2) axpy(c2, h2const(S4 * LM / S2), c4);
    if constexpr (I == PIV + 2) axpy(c3, h2const(S4 * (-DD / A2)), c4);
    if constexpr (I == PIV + 3) { axpy(c1, h2const(-1.f / (2.f * PA)), c2); axpy(c2, h2const(PA), c1); }
    if constexpr (I == PIV + 4) axpy(c4, h2const(A2), c1);
    if constexpr (I == PIV + 5) axpy(c3, h2const(1.f / A2), c2);
  }

  template <int I, int END, bool FIRST = false>
  __device__ __forceinline__ void steps() {
    if constexpr (I < END) {
      constexpr int J = (I + 1) % NSTEP, S = FIRST ? head(I) : I, T = FIRST ? head(J) : J, G = FIRST ? head_gate_of(I) : gate_of(I);
      uint32_t(&d)[48] = step_acc(S) == 0 ? c1 : step_acc(S) == 1 ? c2 : step_acc(S) == 2 ? c3 : c4;
      constexpr int vo = vslot(step_p(S), step_n(S)) * VSLOT, uo = USLOT<I> * USLAB;
      if (!ok) {
        mbar_wait_short(sb + BAR_UFULL + 8 * USLOT<I>, UUSE<I> & 1);
        if constexpr (first_use(step_n(S)) == S) mbar_wait_short(sb + BAR_VFULL + 8 * (step_n(S) % NB), step_n(S) / NB);
      }
      const uint64_t da = descA[FIRST ? 4 : slot_use(I)], db = descB[(FIRST ? 16 : 0) + UUSE<I>];
      wg_fence();
      wgmma192<vo, uo>(d, da, db, first_on(step_acc(S)) == S ? 0u : 1u);
      wgmma192<vo + 16, uo + UTILE>(d, da, db, 1u);
      wgmma192<vo + 32, uo + 2 * UTILE>(d, da, db, 1u);
      wg_commit();
      ok = mbar_test(sb + BAR_UFULL + 8 * USLOT<J>, UUSE<J> & 1);
      if constexpr (first_use(step_n(T)) == T) ok &= mbar_test(sb + BAR_VFULL + 8 * (step_n(T) % NB), step_n(T) / NB);
      if constexpr (!FIRST) hook<I>();
      wg_wait<0>();
      reg_fence(d);
      if (lead) mbar_arrive(sb + BAR_UEMPTY + 8 * USLOT<I>);
      if constexpr (G >= 0) { if (lead) mbar_arrive(sb + BAR_GATE + 8 * (G % NB)); }
      steps<I + 1, END, FIRST>();
    }
  }
  template <int I>
  __device__ __forceinline__ void chain() {
    if constexpr (I < NSTEP) {
      static_assert(step_acc(I) == 3 && NSTEP - I <= NU, "chain");
      constexpr int vo = vslot(step_p(I), step_n(I)) * VSLOT, uo = USLOT<I> * USLAB;
      mbar_wait_short(sb + BAR_UFULL + 8 * USLOT<I>, UUSE<I> & 1);
      const uint64_t da = descA[5], db = descB[21];
      wg_fence();
      wgmma192<vo, uo>(c4, da, db, 1u);
      wgmma192<vo + 16, uo + UTILE>(c4, da, db, 1u);
      wgmma192<vo + 32, uo + 2 * UTILE>(c4, da, db, 1u);
      wg_commit();
      chain<I + 1>();
    }
  }
  template <int I>
  __device__ __forceinline__ void release() {
    if constexpr (I < NSTEP) {
      if (lead) mbar_arrive(sb + BAR_UEMPTY + 8 * USLOT<I>);
      release<I + 1>();
    }
  }
  template <int T>
  __device__ __forceinline__ void finish(bool second) {
    if (second) {
      flush<T, 0, 18>();
      asm volatile("bar.sync 1, 256;" ::: "memory");
    }
    chain<T>();
    if (!second) {
      asm volatile("bar.arrive 1, 256;" ::: "memory");
      flush<T, 0, 18>();
    }
    wg_wait<0>();
    reg_fence(c4);
    release<T>();
    done++;
    flush<T, 18, 24>();
  }
};

struct SlotTab { uint32_t off[NSUB][8]; };
constexpr SlotTab make_slots() {
  SlotTab t = {};
  for (int n = 0; n < NSUB; n++)
    for (int p = 0; p < 6; p++) t.off[n][p] = vslot(p, n) * VSLOT;
  return t;
}
__constant__ __align__(64) SlotTab c_slots = make_slots();

constexpr int PF_X = 22, PF_BYTES = PF_X * 2 * 16, PF_NB = 12, U_LEAD = 10;
static_assert(PF_BYTES + 64 <= OFF_U - OFF_SINK, "sink");
__host__ __device__ constexpr uint32_t pf_box(int k) { return 1u << 31 | (k / PF_NB / 3) << 30 | (k / PF_NB % 3) << 28 | (k % PF_NB) << 24; }
__host__ __device__ constexpr int slab_of(int i) { return step_p(i % NSTEP) * NSUB + step_n(i % NSTEP); }
struct LoadTab { uint32_t e[2 * NSTEP]; };
constexpr LoadTab make_loads() {
  LoadTab t = {};
  constexpr int win[6] = {25, 42, 45, 72, 73, 96};
  for (int k = 0, i = 0; k < 6 * PF_NB; k++) {
    const int g = k / PF_NB % 3, when = win[2 * g] + k % PF_NB * (win[2 * g + 1] - win[2 * g]) / PF_NB - (k < 3 * PF_NB ? NSTEP : 0);
    if (when >= 0 && when < NSTEP) t.e[NSTEP + when] = pf_box(k);
    if (k < PF_NB) continue;
    if (i < when) i = when;
    if (i < NSTEP) t.e[i++] = pf_box(k);
  }
  for (int i = 0; i < 2 * NSTEP; i++) {
    int d = 1;
    while (uslot((i + d) % NSTEP) != uslot(i % NSTEP)) d++;
    if (d > NU + 1) d = 0;
    t.e[i] |= (uuse(i % NSTEP) & 1) << 23 | uslot(i % NSTEP) << 20 | d << 16 | slab_of(i + U_LEAD) << 8 | slab_of(head(i + d));
  }
  return t;
}
__constant__ __align__(64) LoadTab c_load = make_loads();

template <int I>
__device__ __forceinline__ void first_slabs(const uint8_t* u) {
  if constexpr (utrigger(I) < 0) {
    constexpr int slab = slab_of(head(I));
    load_u_warp(SMEM_BASE + OFF_U + USLOT<I> * USLAB, u + slab * USLAB, SMEM_BASE + BAR_UFULL + 8 * USLOT<I>);
    first_slabs<I + 1>(u);
  }
}

template <int BYTES>
__device__ __forceinline__ uint32_t warm(const void* p, uint32_t zero) {
  uint32_t v = ~0u;
#pragma unroll
  for (int o = 0; o < BYTES; o += 64) v &= ((const uint32_t*)p)[o / 4 + zero];
  return v;
}

__global__ void __launch_bounds__(384, 1) __cluster_dims__(1, 1, 1)
conv_kernel(const __grid_constant__ CUtensorMap tmX, const __grid_constant__ CUtensorMap tmH, const __grid_constant__ CUtensorMap tmP,
            const __nv_bfloat16* __restrict__ xin, const __nv_bfloat16* __restrict__ wgt, __nv_bfloat16* __restrict__ out,
            uint4* ubuf, uint32_t* arrived, int nblk, int nlong, int nmax, const __grid_constant__ Descs desc) {
  extern __shared__ uint8_t smem_raw[];
  const int tid = threadIdx.x, lane = tid & 31, bid = blockIdx.x;
  const int pidx = bid - (nblk - NP);
  constexpr uint32_t sb = SMEM_BASE;
  uint32_t epoch = 0;
  if (tid < 256) {
    cluster_arrive_relaxed();
    if (pidx >= 0) {
      const uint32_t t0 = pidx * 8 + (tid >> 5), wsm = sb + OFF_V + (tid >> 5) * NROUND * WTASK;
      prep_load(wsm, wgt, t0, lane);
      const Sample ws = sample_w(wgt, lane);
      const float sw = __uint_as_float(max(253 - (int)sample_exp(ws), 0) << 23);
      const int klane = (lane & 6) * 4 + (lane >> 3) * 2 + (lane & 1);
      int stage = 0;
#pragma unroll 1
      for (int round = 0; round < 2 * NROUND; round++) {
        const int k = round < NROUND ? round : round - NROUND;
        asm volatile("cp.async.wait_all;" ::: "memory");
        __syncwarp();
        float g[3][8];
#pragma unroll
        for (int i = 0; i < 24; i++) {
          uint16_t v;
          asm volatile("ld.shared.u16 %0, [%1];" : "=h"(v) : "r"(wsm + k * WTASK + i * 64 + klane * 2) : "memory");
          g[i / 8][i % 8] = __uint_as_float((uint32_t)v << 16) * sw;
        }
        if (t0 + k * 8 * NP < NTASK) prep_store(g, ubuf, t0 + k * 8 * NP, round >= NROUND, klane);
        if (round + 1 == stage_end(0) || round + 1 == stage_end(1) || round + 1 == stage_end(2)) {
          if (++stage == NSTAGE) {
            fence_async();
            asm volatile("ld.relaxed.gpu.global.u32 %0, [%1];" : "=r"(epoch) : "l"(arrived + 32 * NSTAGE) : "memory");
          }
          asm volatile("bar.sync 1, 256;" ::: "memory");
          if (tid == 0) asm volatile("red.release.gpu.global.add.u32 [%0], %1;" ::"l"(arrived + 32 * stage), "r"(pidx ? 1 : 0x80000001u - NP) : "memory");
          asm volatile("bar.sync 1, 256;" ::: "memory");
          if (stage == 1) {
#pragma unroll 1
            for (int j = 1; j < NROUND; j++) prep_load(wsm + j * WTASK, wgt, t0 + j * 8 * NP, lane);
          }
        }
      }
      if (tid < 32) asm volatile("bar.arrive 2, 64;" ::: "memory");
    } else if (tid < 32) {
      epoch = stage_enter(arrived, lane, 1);
      spin_until(now(), 2200);
    }
  }
  if (tid >= 352) {
    asm volatile("prefetch.tensormap [%0];" ::"l"(&tmX) : "memory");
    constexpr uint64_t twos = ((2ull << NU) - 1) << (BAR_UEMPTY - OFF_BAR) / 8 | ((1ull << 2 * NB) - 1) << (BAR_VFULL - OFF_BAR) / 8;
    constexpr uint64_t threes = ((1ull << NB) - 1) << (BAR_VFULL - OFF_BAR) / 8;
    if (lane == 0) {
#pragma unroll
      for (int i = 0; i < NBAR; i++) mbar_init(sb + OFF_BAR + 8 * i, 1 + ((twos >> i) & 1) + ((threes >> i) & 1));
      asm volatile("fence.mbarrier_init.release.cluster;" ::: "memory");
      fence_async();
    }
    __syncwarp();
    cluster_arrive_relaxed();
    epoch = stage_enter(arrived, lane, pidx ? 1 : 0x80000001u + NP - 2 * nblk);
    if (pidx >= 0) asm volatile("bar.sync 2, 64;" ::: "memory");
    const uint32_t t0 = now();
#pragma unroll 1
    for (int k = 0, box = 0; k < 9; k++, box = box < 6 ? box + 3 : box - 5) {
      if (pidx < 0) spin_until(t0, min(k, 7) * 410);
      tma_box_warp(sb + OFF_X + box * XBOX, k < 8 ? &tmX : &tmH, sb + BAR_XFULL + 8 * box, k < 8 ? XBOX : XHBOX, 0, halo_x(bid) + k * 8,
                   halo_y(bid));
      if (k == 0) asm volatile("prefetch.tensormap [%0];\nprefetch.tensormap [%1];" ::"l"(&tmH), "l"(&tmP) : "memory");
    }
  }
  if (smem_u32(smem_raw) != SMEM_BASE) __trap();
  const int warp = __shfl_sync(0xffffffffu, tid >> 5, 0);

  if (warp < 8) {
    const int wg = warp >> 2;
    if (warp == 7) {
      spin_until(now(), 1300);
      if ((warm<sizeof(SlotTab)>(&c_slots, tid >> 10) & warm<sizeof(LoadTab)>(&c_load, tid >> 10)) == ~0u) __trap();
    }
    cluster_wait();
    if (warp == 0) {
      stage_wait(arrived + 32, __shfl_sync(0xffffffffu, epoch, 0));
      first_slabs<0>((const uint8_t*)ubuf);
    }
    asm volatile("setmaxnreg.inc.sync.aligned.u32 224;");
    Consumer c;
#pragma unroll
    for (int i = 0; i < 48; i++) { c.c1[i] = 0; c.c2[i] = 0; c.c3[i] = 0; c.c4[i] = 0; }
#pragma unroll
    for (int e = 0; e < 4; e++) c.pa[e] = c.pb[e] = c.px[e] = 0;
    c.descA = desc.a[wg];
    c.descB = desc.b;
    c.lead = (tid & 127) == 0;
    c.one = __shfl_sync(0xffffffffu, nblk, 0);
    c.ok = false;
    c.bid = bid;
    c.nblk = nblk;
    c.nlong = nlong;
    c.odd = (lane >> 2) & 1;
    c.pout = (uint8_t*)out + (long long)(region_px(bid - nblk) + wg * 4 * IMG + (warp & 3) * 16 + (lane >> 3) * 2) * (CH * 2) + (lane & 7) * 16;
    c.done = c.osc = c.ymax = c.redo = 0;
    constexpr int ROT = 69;
    c.steps<0, NHEAD, true>();
    bool tail = false;
#pragma unroll 1
    do {
      wg_wait<0>();
      if (tail) {
        c.steps<ROT, NSTEP>();
        c.done++;
        c.steps<0, NHEAD>();
      }
      c.steps<NHEAD, ROT>();
      tail = c.always();
    } while (bid + (int)(c.done + 1) * nblk < NREG);
    c.finish<ROT>(wg);
    c.range_check();
    if (c.redo >> 1) {
      __syncwarp();
      for (int i = 0; i < (int)c.done; i++)
        if ((c.redo >> (i + 1)) & 1) {
          const int r = bid + i * nblk;
          direct_patch(xin, wgt, out, (r >> 3) * 8 + wg * 4, (r & 7) * 64 + (warp & 3) * 16, lane);
        }
    }
  } else {
    asm volatile("setmaxnreg.dec.sync.aligned.u32 56;");
    const int nitem = nmax - (bid >= nlong);
    if (warp == 11) {
      const uint8_t* ubase = (const uint8_t*)ubuf;
      epoch = __shfl_sync(0xffffffffu, epoch, 0);
      cluster_wait();
      const uint8_t* uline = ubase + (bid * 2 + lane) * 128;
      const bool ufetch = lane < 2 && bid < USLAB / 256;
      int r = bid, npf = 0;
      int i = 0, tab = 0;
#pragma unroll 1
      for (int left = nitem * NSTEP - 1; left >= 0; left--) {
        const uint32_t e = c_load.e[tab + i], slot = (e >> 20) & 7;
        const uint8_t* src = ubase + (e & 255) * USLAB;
        const uint8_t* pu = uline + ((e >> 8) & 255) * USLAB;
        const uint32_t dst = sb + OFF_U + slot * USLAB, ebar = sb + BAR_UEMPTY + 8 * slot;
        const bool refill = ((e >> 16) & 7) - 1 < (uint32_t)left;
        constexpr int need1 = utrigger(stage_first(1)), need2 = utrigger(stage_first(2)), xslab = slab_of(UX_FIRST);
        if (tab + i == need1 || tab + i == need2) stage_wait(arrived + (i == need1 ? 64 : 96), epoch);
        refill_u(ebar, (e >> 23) & 1, refill, dst, src);
        if (i == UX_GATE) load_u_warp(sb + OFF_V, ubase + xslab * USLAB, sb + BAR_UFULL + 8 * NU);
        const int rr = r + ((e >> 30) & 1) * nblk;
        if ((int)e < 0 && rr < NREG) {
          asm volatile("{\n.reg .pred p;\nelect.sync _|p, 0xffffffff;\n"
                       "@p cp.async.bulk.tensor.3d.shared::cluster.global.mbarrier::complete_tx::bytes [%0], [%1, {%3, %4, %5}], [%2];\n}\n"
                       ::"r"(sb + OFF_SINK), "l"(&tmP), "r"(sb + BAR_SINK), "r"((e >> 22) & 0xC0), "r"(halo_x(rr) + ((e >> 26) & 3) * PF_X),
                       "r"(halo_y(rr) + 1 + ((e >> 23) & 6)) : "memory");
          npf++;
        }
        if (ufetch && tab + i >= NSTEP - U_LEAD && left >= U_LEAD)
          asm volatile("cp.async.ca.shared.global.L2::128B [%0], [%1], 4;" ::"r"(sb + OFF_SINK + PF_BYTES + lane * 4), "l"(pu) : "memory");
        if (++i == NSTEP) { i = 0; r += nblk; tab = NSTEP; }
      }
      if (lane == 0) asm volatile("mbarrier.arrive.expect_tx.shared::cta.b64 _, [%0], %1;" ::"r"(sb + BAR_SINK), "r"(npf * PF_BYTES) : "memory");
      mbar_wait(sb + BAR_SINK, 0);
      asm volatile("cp.async.wait_all;" ::: "memory");
    } else {
      cluster_arrive_relaxed();
      const int w = warp - 8, col = (lane >> 1) & 7, chunk = lane >> 4;
      const uint32_t xbox = sb + OFF_X + w * 3 * XBOX, xbar = sb + BAR_XFULL + 24 * w;
      const uint32_t xl = xbox + col * 32 + ((chunk ^ (col >> 2)) << 4) + (lane & 1) * 8;
      const uint32_t vl = sb + OFF_V + chunk * VROW + w * 128 + (lane & 15) * 8;
      const bool in_row = w < 2 || col < 2;
      const uint32_t pitch2 = w < 2 ? 256 : 64, bytes2 = 10 * pitch2;
      const uint32_t xl2 = w < 2 ? xl + 2 * XBOX : xbox + 2 * XBOX + col * 32 + chunk * 16 + (lane & 1) * 8;
      const CUtensorMap* tm2 = w < 2 ? &tmX : &tmH;
      auto xrow = [&](int j, int i) {
        uint2 v = make_uint2(0, 0);
        if (j < 2 || in_row) v = lds64(j < 2 ? xl + j * XBOX + i * 256 : xl2 + i * pitch2);
        return v;
      };
      const Sample ws = sample_w(wgt, lane), xs = sample_x(xin, bid, lane);
      uint32_t xsc;
      {
        const int ex = sample_exp(xs), eo = ex + (int)sample_exp(ws) - (111 + X_EXP), es = 127 + X_EXP - ex;
        xsc = es >= 1 && eo >= 1 && eo <= 254 ? es * 0x00800080u : NAN2;
        asm volatile("st.shared.u32 [%0], %1;" ::"r"(sb + OFF_OSC), "r"(eo * 0x00800080u) : "memory");
      }
      constexpr uint32_t gate_par = [] { uint32_t m = 0; for (int n = 0; n < NSUB; n++) if ((n / NB) ^ (gate(n % NB) < 0)) m |= 1u << n; return m; }();
      constexpr uint32_t LIM2 = X_LIM * 0x10001u;
      cluster_wait();
      auto conv = [&](uint2& v, uint32_t m) {
        const uint32_t tx = bmul2(v.x, xsc), ty = bmul2(v.y, xsc), ux = tx & NAN2, uy = ty & NAN2;
        v = make_uint2(ux * 7 + tx, uy * 7 + ty);
        return __vimax3_u16x2(m, ux, uy);
      };
      uint32_t so[6] = {};
      auto planes = [&](const uint2* h, uint32_t m, uint32_t a, bool on) {
        constexpr uint32_t NB2 = h2const(-B2), NA2 = h2const(-A2);
        const uint2 e1 = fma4(NB2, h[2], h[4]), e2 = fma4(NA2, h[2], h[4]);
        store_v(a + so[4], fma4(NA2, fma4(NB2, h[0], h[2]), e1), on);
        const uint2 o1 = fma4(NB2, h[1], h[3]), o2 = fma4(NA2, h[1], h[3]);
        store_v(a + so[5], fma4(NA2, o1, fma4(NB2, h[3], h[5])), on);
        uint2 v = fma4(h2const(PA), o1, e1);
        if (m != LIM2) v.x = NAN2;
        store_v(a + so[0], v, on);
        store_v(a + so[1], fma4(h2const(-PA), o1, e1), on);
        store_v(a + so[2], fma4(h2const(PB), o2, e2), on);
        store_v(a + so[3], fma4(h2const(-PB), o2, e2), on);
      };
      int r = bid, n = 0;
      uint32_t par = 0;
#pragma unroll 1
      for (int left = nitem * NSUB; left > 0; left--) {
        const int nb = n >= NB ? n - NB : n;
        uint2 d[10];
        mbar_wait(xbar, par);
#pragma unroll
        for (int i = 0; i < 6; i++) d[i] = xrow(0, i);
#pragma unroll
        for (int p = 0; p < 6; p++) so[p] = c_slots.off[n][p];
        const uint32_t gpar = (gate_par >> n) & 1;
        if (++n == NSUB) { n = 0; r += nblk; }
        const int fc = n * 16, fx = halo_x(r) + w * 8, fy = halo_y(r);
#pragma unroll
        for (int j = 0; j < 3; j++) {
          const bool on = j < 2 || in_row;
#pragma unroll
          for (int i = 6; i < 10; i++) d[i] = xrow(j, i);
          const bool xok = j < 2 && mbar_test(xbar + 8 * (j + 1), par);
          sched_barrier();
          const uint32_t m45 = conv(d[5], conv(d[4], LIM2));
          const uint32_t ma = conv(d[3], conv(d[1], conv(d[0], conv(d[2], m45))));
          if (j == 0) mbar_wait(sb + BAR_GATE + 8 * nb, gpar);
          planes(d, ma, vl + j * 384, on);
          sched_barrier();
          const uint32_t mb = conv(d[9], conv(d[7], conv(d[6], conv(d[8], m45))));
          if (left > 1) tma_box_warp(xbox + j * XBOX, j < 2 ? &tmX : tm2, xbar + 8 * j, (j < 2 ? XBOX : bytes2) | (mb & 0x8000u), fc, fx + j * 24, fy);
          uint2 h[6];
#pragma unroll
          for (int i = 0; i < 6; i++) h[i] = d[4 + i];
          if (j < 2) {
            mbar_wait(xbar + 8 * (j + 1), par, xok);
#pragma unroll
            for (int i = 0; i < 6; i++) d[i] = xrow(j + 1, i);
          }
          sched_barrier();
          planes(h, mb, vl + j * 384 + VPIECE, on);
          sched_barrier();
        }
        fence_async();
        asm volatile("{\n.reg .pred p;\nelect.sync _|p, 0xffffffff;\n@p mbarrier.arrive.shared::cta.b64 _, [%0];\n}\n" ::"r"(sb + BAR_VFULL + 8 * nb) : "memory");
        par ^= 1;
      }
    }
  }
}

constexpr uint64_t make_desc(uint32_t off, uint32_t lbo, uint32_t sbo) {
  return (uint64_t)((SMEM_BASE + off) >> 4) | ((uint64_t)(lbo >> 4) << 16) | ((uint64_t)(sbo >> 4) << 32);
}

typedef CUresult (*EncodeFn)(CUtensorMap*, CUtensorMapDataType, cuuint32_t, void*, const cuuint64_t*, const cuuint64_t*,
                             const cuuint32_t*, const cuuint32_t*, CUtensorMapInterleave, CUtensorMapSwizzle,
                             CUtensorMapL2promotion, CUtensorMapFloatOOBfill);

}

extern "C" void kernel_launch(void* const* d_in, const int* in_sizes, int n_in, void* d_out, int out_size) {
  static EncodeFn enc = nullptr;
  static int nblk = 0;
  static uint4* ubuf;
  static uint32_t* arrived;
  if (!enc) {
    cudaGetSymbolAddress((void**)&ubuf, g_U);
    cudaGetSymbolAddress((void**)&arrived, g_arrived);
    cudaDriverEntryPointQueryResult qr;
    cudaGetDriverEntryPoint("cuTensorMapEncodeTiled", (void**)&enc, cudaEnableDefault, &qr);
    cudaFuncSetAttribute(conv_kernel, cudaFuncAttributeMaxDynamicSharedMemorySize, SMEM_BYTES);
    int dev;
    cudaGetDevice(&dev);
    cudaDeviceGetAttribute(&nblk, cudaDevAttrMultiProcessorCount, dev);
  }
  CUtensorMap tmX, tmH, tmP;
  const cuuint64_t dims[3] = {CH, IMG, IMG};
  const cuuint64_t strides[2] = {CH * 2, (cuuint64_t)CH * 2 * IMG};
  const cuuint32_t es[3] = {1, 1, 1};
  const cuuint32_t boxX[3] = {16, 8, 10}, boxH[3] = {16, 2, 10}, boxP[3] = {8, PF_X, 2};
  enc(&tmH, CU_TENSOR_MAP_DATA_TYPE_BFLOAT16, 3, d_in[0], dims, strides, boxH, es, CU_TENSOR_MAP_INTERLEAVE_NONE,
      CU_TENSOR_MAP_SWIZZLE_NONE, CU_TENSOR_MAP_L2_PROMOTION_L2_64B, CU_TENSOR_MAP_FLOAT_OOB_FILL_NONE);
  enc(&tmP, CU_TENSOR_MAP_DATA_TYPE_BFLOAT16, 3, d_in[0], dims, strides, boxP, es, CU_TENSOR_MAP_INTERLEAVE_NONE,
      CU_TENSOR_MAP_SWIZZLE_NONE, CU_TENSOR_MAP_L2_PROMOTION_L2_128B, CU_TENSOR_MAP_FLOAT_OOB_FILL_NONE);
  enc(&tmX, CU_TENSOR_MAP_DATA_TYPE_BFLOAT16, 3, d_in[0], dims, strides, boxX, es, CU_TENSOR_MAP_INTERLEAVE_NONE,
      CU_TENSOR_MAP_SWIZZLE_32B, CU_TENSOR_MAP_L2_PROMOTION_L2_64B, CU_TENSOR_MAP_FLOAT_OOB_FILL_NONE);
  Descs desc = {};
  for (int i = 0; i < 6; i++) { desc.a[0][i] = make_desc(OFF_V, VROW, 128); desc.a[1][i] = make_desc(OFF_V + VPIECE, VROW, 128); }
  for (int i = 0; i < 22; i++) desc.b[i] = make_desc(OFF_U, 128, 256);
  conv_kernel<<<nblk, 384, SMEM_BYTES>>>(tmX, tmH, tmP, (const __nv_bfloat16*)d_in[0], (const __nv_bfloat16*)d_in[1], (__nv_bfloat16*)d_out, ubuf, arrived, nblk,
                                         NREG % nblk ? NREG % nblk : nblk, (NREG + nblk - 1) / nblk, desc);
}
```

```cpp
#include <cuda_runtime.h>
#include <cuda_bf16.h>
#include <cuda.h>
#include <stdint.h>

namespace {

constexpr int IMG = 512, CH = 192;
constexpr float PA = 1.5f, PB = 0.6875f;
constexpr float A2 = PA * PA, B2 = PB * PB, DD = B2 - A2;

constexpr int NSTEP = 72, NSUB = 12;
__host__ __device__ constexpr int sched(int i) {
  constexpr int t[NSTEP] = {
      0x00, 0x10, 0x20, 0x01, 0x11, 0x21, 0x02, 0x12, 0x22, 0x03, 0x13, 0x23, 0x30, 0x31, 0x32, 0x33, 0x24, 0x34,
      0x04, 0x14, 0x25, 0x35, 0x05, 0x15, 0x26, 0x36, 0x06, 0x16, 0x27, 0x37, 0x07, 0x17, 0x28, 0x38, 0x08, 0x18,
      0x29, 0x39, 0x09, 0x19, 0x2a, 0x3a, 0x0a, 0x1a, 0x2b, 0x3b, 0x1b, 0x0b, 0x40, 0x4b, 0x50, 0x41, 0x51, 0x4a,
      0x49, 0x48, 0x47, 0x42, 0x52, 0x46, 0x45, 0x5b, 0x44, 0x43, 0x5a, 0x53, 0x59, 0x58, 0x57, 0x56, 0x54, 0x55};
  return t[i];
}
__host__ __device__ constexpr int step_p(int i) { return sched(i) >> 4; }
__host__ __device__ constexpr int step_n(int i) { return sched(i) & 15; }
__host__ __device__ constexpr int step_acc(int i) { return step_p(i) < 4 ? step_p(i) : step_p(i) - 2; }
__host__ __device__ constexpr int first_on(int acc) {
  for (int i = 0; i < NSTEP; i++)
    if (step_acc(i) == acc) return i;
  return -1;
}
__host__ __device__ constexpr int last_on(int acc) {
  for (int i = NSTEP - 1; i >= 0; i--)
    if (step_acc(i) == acc) return i;
  return -1;
}
__host__ __device__ constexpr int find_step(int p, int n) {
  for (int i = 0; i < NSTEP; i++)
    if (sched(i) == p * 16 + n) return i;
  return -1;
}
__host__ __device__ constexpr int first_use(int n) {
  for (int i = 0; i < NSTEP; i++)
    if (step_n(i) == n) return i;
  return -1;
}
constexpr int NHEAD = first_on(3) / 3 * 4;
__host__ __device__ constexpr int head(int i) { return i < NHEAD ? find_step(i % 4, i / 4) : i; }
constexpr float S1 = 1.f / PA, S2 = 1.f / (2.f * A2), S3 = -A2 / (2.f * DD), S4 = -1.f / (PB * DD);
constexpr int PIV = find_step(3, NSUB - 1);
static_assert(find_step(2, NSUB - 1) == PIV - 1 && last_on(1) == PIV + 1 && last_on(0) == PIV + 2 && PIV + 3 == 4 * NSUB &&
              step_p(PIV + 3) == 4 && step_p(PIV + 4) == 4 && step_p(PIV + 5) == 5, "basis change");

constexpr int NV = 32, NB = 6;
__host__ __device__ constexpr int vslot(int p, int n) {
  constexpr int t[6][NSUB] = {
      {31, 19, 25, 18, 19, 27, 21, 4, 24, 26, 3, 26}, {28, 23, 24, 22, 17, 24, 28, 3, 25, 27, 0, 28}, {27, 17, 14,
      20, 23, 22, 20, 31, 0, 28, 1, 2}, {26, 21, 15, 16, 31, 18, 23, 26, 23, 31, 4, 31}, {7, 6, 8, 10, 12, 14, 15,
      17, 19, 21, 23, 27}, {30, 29, 9, 11, 13, 5, 16, 18, 20, 22, 24, 25}};
  return t[p][n];
}
__host__ __device__ constexpr int gate(int n) {
  constexpr int t[NSUB] = {-20, -14, -8, -2, 5, 11, 16, 21, 25, 29, 34, 39};
  return t[n];
}
__host__ __device__ constexpr int gate_of(int i) {
  for (int n = 0; n < NSUB; n++)
    if ((gate(n) + NSTEP) % NSTEP == i) return n;
  return -1;
}
__host__ __device__ constexpr int head_gate_of(int i) {
  for (int n = 0; n < NSUB; n++) {
    int m = -1;
    for (int j = 0; j < NHEAD; j++)
      if (head(j) <= gate(n)) m = j;
    if (gate(n) < NHEAD && m == i) return n;
  }
  return -1;
}
__host__ __device__ constexpr bool gates_ok() {
  int early = 0;
  for (int i = 0; i < NHEAD; i++) early += (gate_of(i) >= 0) - (head_gate_of(i) >= 0) + (head(i) >= NHEAD);
  if (early) return false;
  for (int n = 0; n < NSUB; n++) {
    for (int p = 0; p < 6; p++)
      for (int d = 1; d <= NSUB; d++)
        for (int q = 0; q < 6; q++) {
          const int m = (n - d + NSUB) % NSUB;
          if (vslot(q, m) == vslot(p, n) && (find_step(q, m) - (n - d < 0 ? NSTEP : 0) > gate(n) || (m == n && p != q))) return false;
        }
    if (n > 0 && (gate(n) <= gate(n - 1) || first_use(n) <= first_use(n - 1))) return false;
    if (gate(n) >= first_use(n)) return false;
    if (gate((n + NB) % NSUB) + (n >= NB ? NSTEP : 0) < first_use(n)) return false;
  }
  return gate(0) + NSTEP > gate(NSUB - 1) && gate(NB) >= 0;
}
static_assert(gates_ok(), "gates");

constexpr int UTILE = CH * 16 * 2;
constexpr int USLAB = 3 * UTILE;
constexpr int NU = 4;
constexpr int VROW = 66 * 16;
constexpr int VPIECE = 2 * VROW;
constexpr int VSLOT = 2 * VPIECE;
constexpr int XBOX = 10 * 8 * 32;
constexpr int XHBOX = 10 * 2 * 32;
constexpr int UX_FIRST = 52, UX_COUNT = 8, UX_GATE = UX_FIRST - NU - 1;
__host__ __device__ constexpr bool uextra(int i) {
  const int d = (i - UX_FIRST + NSTEP) % NSTEP;
  return d % (NU + 1) == 0 && d / (NU + 1) < UX_COUNT;
}
__host__ __device__ constexpr int uindex(int i) {
  int c = 0;
  for (int j = 0; j < i; j++) c += uextra(j) == uextra(i);
  return c;
}
__host__ __device__ constexpr int uslot(int i) { return uextra(i) ? NU : uindex(i) % NU; }
__host__ __device__ constexpr int uuse(int i) { return uextra(i) ? uindex(i) : uindex(i) / NU; }
__host__ __device__ constexpr int utrigger(int j) {
  if (j == UX_FIRST) return UX_GATE;
  int i = j - 1;
  while (uslot((i + NSTEP) % NSTEP) != uslot(j)) i--;
  return i;
}
template <int I> constexpr int USLOT = uslot(I);
template <int I> constexpr int UUSE = uuse(I);
__host__ __device__ constexpr bool uring_ok() {
  for (int n = 0; n < NSUB; n++)
    for (int p = 0; p < 6; p++)
      if (vslot(p, n) * VSLOT < USLAB &&
          (find_step(p, n) > UX_GATE || gate(n) < UX_FIRST + (NU + 1) * (UX_COUNT - 1) - NSTEP))
        return false;
  return UX_COUNT % 2 == 0 && (NSTEP - UX_COUNT) % (2 * NU) == 0;
}
static_assert(uring_ok(), "U ring");

constexpr int OFF_X = 0;
constexpr int OFF_SINK = OFF_X + 8 * XBOX + XHBOX;
constexpr int OFF_U = OFF_SINK + 768;
constexpr int OFF_V = OFF_U + NU * USLAB;
constexpr int OFF_BAR = OFF_V + NV * VSLOT;
constexpr int BAR_UFULL = OFF_BAR;
constexpr int BAR_UEMPTY = BAR_UFULL + 8 * (NU + 1);
constexpr int BAR_XFULL = BAR_UEMPTY + 8 * (NU + 1);
constexpr int BAR_VFULL = BAR_XFULL + 8 * 9;
constexpr int BAR_GATE = BAR_VFULL + 8 * NB;
constexpr int BAR_SINK = BAR_GATE + 8 * NB;
constexpr int OFF_OSC = BAR_SINK + 8;
constexpr int NBAR = (OFF_OSC - OFF_BAR) / 8;
constexpr int OFF_REDO = OFF_OSC + 8;
constexpr int SMEM_BYTES = OFF_REDO + 256;
constexpr uint32_t SMEM_BASE = 1024;
static_assert(SMEM_BYTES <= 232448, "smem");

constexpr int NREG = 512;

__device__ __align__(128) uint4 g_U[NSTEP * USLAB / 16];
__device__ uint32_t g_arrived[4 * 32];

__device__ __forceinline__ uint32_t smem_u32(const void* p) { return (uint32_t)__cvta_generic_to_shared(p); }
__device__ __forceinline__ void mbar_init(uint32_t a, int c) {
  asm volatile("mbarrier.init.shared::cta.b64 [%0], %1;" ::"r"(a), "r"(c) : "memory");
}
__device__ __forceinline__ void mbar_arrive(uint32_t a) {
  asm volatile("mbarrier.arrive.shared::cta.b64 _, [%0];" ::"r"(a) : "memory");
}
__device__ __forceinline__ void mbar_wait(uint32_t a, uint32_t parity, uint32_t skip = 0) {
  asm volatile(
      "{\n"
      ".reg .pred p;\n"
      ".reg .u32 n;\n"
      "setp.ne.u32 p, %2, 0;\n"
      "@p bra.uni LAB_DONE;\n"
      "mov.u32 n, 0;\n"
      "LAB_WAIT:\n"
      "mbarrier.try_wait.parity.shared::cta.b64 p, [%0], %1;\n"
      "@p bra.uni LAB_DONE;\n"
      "add.u32 n, n, 1;\n"
      "setp.lt.u32 p, n, 4000000;\n"
      "@p bra.uni LAB_WAIT;\n"
      "trap;\n"
      "LAB_DONE:\n"
      "}\n" ::"r"(a), "r"(parity), "r"(skip) : "memory");
}
__device__ __forceinline__ void mbar_wait_short(uint32_t a, uint32_t parity) {
  asm volatile("{\n.reg .pred p;\nLAB_WAIT:\nmbarrier.try_wait.parity.shared::cta.b64 p, [%0], %1;\n@!p bra.uni LAB_WAIT;\n}\n" ::"r"(a),
               "r"(parity) : "memory");
}
__device__ __forceinline__ bool mbar_test(uint32_t a, uint32_t parity) {
  uint32_t ok;
  asm volatile("{\n.reg .pred p;\nmbarrier.test_wait.parity.shared::cta.b64 p, [%1], %2;\nselp.u32 %0, 1, 0, p;\n}\n"
               : "=r"(ok) : "r"(a), "r"(parity) : "memory");
  return ok;
}
__device__ __forceinline__ void fence_async() { asm volatile("fence.proxy.async.shared::cta;" ::: "memory"); }
__device__ __forceinline__ void tma_box_warp(uint32_t dst, const CUtensorMap* tm, uint32_t bar, uint32_t bytes, int c, int x, int y) {
  asm volatile(
      "{\n.reg .pred p;\nelect.sync _|p, 0xffffffff;\n"
      "@p mbarrier.arrive.expect_tx.shared::cta.b64 _, [%2], %6;\n"
      "@p cp.async.bulk.tensor.3d.shared::cluster.global.mbarrier::complete_tx::bytes [%0], [%1, {%3, %4, %5}], [%2];\n}\n" ::"r"(dst),
      "l"(tm), "r"(bar), "r"(c), "r"(x), "r"(y), "r"(bytes) : "memory");
}
__device__ __forceinline__ void load_u_warp(uint32_t dst, const void* src, uint32_t bar) {
  asm volatile("{\n.reg .pred p;\nelect.sync _|p, 0xffffffff;\n"
               "@p mbarrier.arrive.expect_tx.shared::cta.b64 _, [%2], %3;\n"
               "@p cp.async.bulk.shared::cluster.global.mbarrier::complete_tx::bytes [%0], [%1], %3, [%2];\n}\n" ::"r"(dst),
               "l"(src), "r"(bar), "n"(USLAB) : "memory");
}
__device__ __forceinline__ void refill_u(uint32_t ebar, uint32_t parity, uint32_t on, uint32_t dst, const void* src) {
  asm volatile(
      "{\n.reg .pred p;\n.reg .u32 n;\n"
      "mov.u32 n, 0;\n"
      "LAB_WAIT:\n"
      "mbarrier.try_wait.parity.shared::cta.b64 p, [%0], %1;\n"
      "@p bra.uni LAB_DONE;\n"
      "add.u32 n, n, 1;\nsetp.lt.u32 p, n, 4000000;\n"
      "@p bra.uni LAB_WAIT;\n"
      "trap;\n"
      "LAB_DONE:\n"
      "setp.eq.u32 p, %2, 0;\n"
      "@p bra.uni LAB_OUT;\n"
      "elect.sync _|p, 0xffffffff;\n"
      "@p mbarrier.arrive.expect_tx.shared::cta.b64 _, [%5], %6;\n"
      "@p cp.async.bulk.shared::cluster.global.mbarrier::complete_tx::bytes [%3], [%4], %6, [%5];\n"
      "LAB_OUT:\n}\n" ::"r"(ebar), "r"(parity), "r"(on), "r"(dst), "l"(src), "r"(ebar - (BAR_UEMPTY - BAR_UFULL)), "n"(USLAB) : "memory");
}
__device__ __forceinline__ uint2 lds64(uint32_t a) {
  uint2 v;
  asm volatile("ld.shared.v2.u32 {%0,%1}, [%2];" : "=r"(v.x), "=r"(v.y) : "r"(a) : "memory");
  return v;
}
__device__ __forceinline__ uint32_t lds32(uint32_t a) {
  uint32_t v;
  asm volatile("ld.shared.u32 %0, [%1];" : "=r"(v) : "r"(a) : "memory");
  return v;
}
__device__ __forceinline__ void store_v(uint32_t a, uint2 v, bool on) {
  v.x &= 0xFFFCFFFCu; v.y &= 0xFFFCFFFCu;
  if (on) asm volatile("st.shared.v2.u32 [%0], {%1,%2};" ::"r"(a), "r"(v.x), "r"(v.y) : "memory");
}
__device__ __forceinline__ void sched_barrier() { asm volatile("pmevent 0;" ::: "memory"); }
__device__ __forceinline__ void spin_cycles(uint32_t n) {
  asm volatile(
      "{\n.reg .pred p;\n.reg .u32 t0, t;\n"
      "mov.u32 t0, %%clock;\n"
      "LAB_SPIN:\n"
      "nanosleep.u32 50;\n"
      "mov.u32 t, %%clock;\nsub.u32 t, t, t0;\nsetp.lt.u32 p, t, %0;\n"
      "@p bra.uni LAB_SPIN;\n}\n" ::"r"(n) : "memory");
}
__device__ __forceinline__ void spin_until(uint32_t t0, uint32_t n) {
  asm volatile("{\n.reg .pred p;\n.reg .u32 t;\nLAB_SPIN:\nmov.u32 t, %%clock;\nsub.u32 t, t, %0;\nsetp.lt.u32 p, t, %1;\n@p bra.uni LAB_SPIN;\n}\n" ::"r"(t0),
               "r"(n) : "memory");
}
__device__ __forceinline__ uint32_t now() {
  uint32_t t;
  asm volatile("mov.u32 %0, %%clock;" : "=r"(t)::"memory");
  return t;
}
__device__ __forceinline__ uint32_t stage_enter(uint32_t* ctr, int lane, uint32_t inc) {
  uint32_t old;
  asm volatile("{\n.reg .pred p;\nsetp.eq.u32 p, %2, 0;\nld.relaxed.gpu.global.u32 %0, [%1];\n@p red.relaxed.gpu.global.add.u32 [%1], %3;\n}"
               : "=r"(old) : "l"(ctr), "r"(lane), "r"(inc) : "memory");
  return old;
}
__device__ __forceinline__ void stage_wait(const uint32_t* ctr, uint32_t old) {
  asm volatile(
      "{\n.reg .pred p;\n.reg .u32 v, i;\n"
      "mov.u32 i, 0;\n"
      "LAB_POLL:\n"
      "ld.acquire.gpu.global.u32 v, [%0];\n"
      "xor.b32 v, v, %1;\nsetp.lt.s32 p, v, 0;\n"
      "@p bra.uni LAB_OUT;\n"
      "add.u32 i, i, 1;\nsetp.lt.u32 p, i, 4000000;\n"
      "@p bra.uni LAB_POLL;\n"
      "trap;\n"
      "LAB_OUT:\n"
      "fence.proxy.async.global;\n}\n" ::"l"(ctr), "r"(old) : "memory");
}
__device__ __forceinline__ void cluster_arrive_relaxed() { asm volatile("barrier.cluster.arrive.relaxed.aligned;" ::: "memory"); }
__device__ __forceinline__ void cluster_wait() { asm volatile("barrier.cluster.wait.acquire.aligned;" ::: "memory"); }

__host__ __device__ constexpr uint32_t h2const(float v) {
  double a = v < 0 ? -v : v;
  int e = 15;
  while (a >= 2) { a /= 2; e++; }
  while (a < 1) { a *= 2; e--; }
  const uint32_t h = (v < 0 ? 0x8000u : 0u) | ((e << 10) + (uint32_t)((a - 1) * 1024 + 0.5));
  return h | h << 16;
}
__device__ __forceinline__ uint32_t hfma2(uint32_t a, uint32_t b, uint32_t c) {
  uint32_t d;
  asm("fma.rn.f16x2 %0, %1, %2, %3;" : "=r"(d) : "r"(a), "r"(b), "r"(c));
  return d;
}
__device__ __forceinline__ uint32_t bmul2(uint32_t a, uint32_t b) {
  uint32_t d;
  asm("mul.rn.bf16x2 %0, %1, %2;" : "=r"(d) : "r"(a), "r"(b));
  return d;
}
__device__ __forceinline__ uint2 fma4(uint32_t k, const uint2& a, const uint2& c) { return make_uint2(hfma2(k, a.x, c.x), hfma2(k, a.y, c.y)); }
__device__ __forceinline__ uint32_t pack_bf16(float lo, float hi) {
  uint32_t d;
  asm("cvt.rn.bf16x2.f32 %0, %1, %2;" : "=r"(d) : "f"(hi), "f"(lo));
  return d;
}
__device__ __forceinline__ uint32_t pack_f16(float lo, float hi) {
  uint32_t d;
  asm("cvt.rn.f16x2.f32 %0, %1, %2;" : "=r"(d) : "f"(hi), "f"(lo));
  return d;
}

template <int AOFF, int BOFF>
__device__ __forceinline__ void wgmma192(uint32_t (&d)[48], uint64_t da, uint64_t db, uint32_t scale_d) {
  asm volatile(
      "{\n.reg .pred p;\n.reg .b64 qa, qb;\n"
      "setp.ne.b32 p, %50, 0;\n"
      "add.s64 qa, %48, %51;\nadd.s64 qb, %49, %52;\n"
      "wgmma.mma_async.sync.aligned.m64n192k16.f16.f16.f16 "
      "{%0, %1, %2, %3, %4, %5, %6, %7, %8, %9, %10, %11, %12, %13, %14, %15, "
      "%16, %17, %18, %19, %20, %21, %22, %23, %24, %25, %26, %27, %28, %29, %30, %31, "
      "%32, %33, %34, %35, %36, %37, %38, %39, %40, %41, %42, %43, %44, %45, %46, %47}, "
      "qa, qb, p, 1, 1, 0, 0;\n}\n"
      : "+r"(d[0]), "+r"(d[1]), "+r"(d[2]), "+r"(d[3]), "+r"(d[4]), "+r"(d[5]), "+r"(d[6]), "+r"(d[7]), "+r"(d[8]),
        "+r"(d[9]), "+r"(d[10]), "+r"(d[11]), "+r"(d[12]), "+r"(d[13]), "+r"(d[14]), "+r"(d[15]), "+r"(d[16]),
        "+r"(d[17]), "+r"(d[18]), "+r"(d[19]), "+r"(d[20]), "+r"(d[21]), "+r"(d[22]), "+r"(d[23]), "+r"(d[24]),
        "+r"(d[25]), "+r"(d[26]), "+r"(d[27]), "+r"(d[28]), "+r"(d[29]), "+r"(d[30]), "+r"(d[31]), "+r"(d[32]),
        "+r"(d[33]), "+r"(d[34]), "+r"(d[35]), "+r"(d[36]), "+r"(d[37]), "+r"(d[38]), "+r"(d[39]), "+r"(d[40]),
        "+r"(d[41]), "+r"(d[42]), "+r"(d[43]), "+r"(d[44]), "+r"(d[45]), "+r"(d[46]), "+r"(d[47])
      : "l"(da), "l"(db), "r"(scale_d), "n"(AOFF >> 4), "n"(BOFF >> 4));
}
__device__ __forceinline__ void wg_fence() { asm volatile("wgmma.fence.sync.aligned;" ::: "memory"); }
__device__ __forceinline__ void wg_commit() { asm volatile("wgmma.commit_group.sync.aligned;" ::: "memory"); }
template <int N>
__device__ __forceinline__ void wg_wait() { asm volatile("wgmma.wait_group.sync.aligned %0;" ::"n"(N) : "memory"); }
__device__ __forceinline__ void reg_fence(uint32_t (&d)[48]) {
#pragma unroll
  for (int i = 0; i < 48; i++) asm volatile("" : "+r"(d[i])::"memory");
}

constexpr uint32_t X_EXP = 17;
constexpr uint32_t X_LIM = ((15 + 8) << 7) - 1;
constexpr uint32_t U_LIM = ((15 + 6) << 10) - 1;
constexpr float W_MIN = 1.f / 8192;
constexpr uint32_t Y_MIN = 0x3C00, Y_INF = 0x7C00;
constexpr uint32_t NAN2 = 0x7FFF7FFFu;
using Sample = uint4;
__device__ __forceinline__ uint4 ldg128(const uint4* p) {
  uint4 v;
  asm volatile("ld.global.v4.u32 {%0,%1,%2,%3}, [%4];" : "=r"(v.x), "=r"(v.y), "=r"(v.z), "=r"(v.w) : "l"(p));
  return v;
}
__device__ __forceinline__ Sample sample_w(const __nv_bfloat16* w, int lane) {
  const int q = lane >> 3;
  return ldg128((const uint4*)(w + ((q == 0 ? 1 : q == 1 ? 3 : 4) * CH + 47 * q) * CH + 64 * (q % 3)) + (lane & 7));
}
__device__ __forceinline__ Sample sample_x(const __nv_bfloat16* x, int r, int lane) {
  return ldg128((const uint4*)(x + (size_t)(((r >> 3) * 8 + 1 + lane % 6) * IMG + (r & 7) * 64 + 2 * lane) * CH) + lane % 24);
}
__device__ __forceinline__ uint32_t sample_exp(const Sample& s) {
  const uint32_t m = __vmaxu2(__vimax3_u16x2(s.x & NAN2, s.y & NAN2, s.z & NAN2), s.w & NAN2);
  return __reduce_max_sync(0xffffffffu, max(m & 0xFFFFu, m >> 16)) >> 7;
}

constexpr int NP = 16, NTASK = NSUB * 36, NROUND = (NTASK + 8 * NP - 1) / (8 * NP), NSTAGE = 3;
__host__ __device__ constexpr int stage_end(int k) { return k == 0 ? 1 : k == 1 ? 3 : 2 * NROUND; }
__host__ __device__ constexpr int stage_first(int k) {
  for (int i = 0; i < NSTEP; i++)
    if (step_p(head(i)) / 4 * NROUND * 8 * NP + (step_n(head(i)) + 1) * 36 > stage_end(k - 1) * 8 * NP) return i;
  return -1;
}
static_assert(utrigger(stage_first(1)) >= 0 && stage_first(2) > stage_first(1), "stages");
struct Task {
  uint32_t n, s, kh, k;
  __device__ __forceinline__ Task(uint32_t t, int lane) {
    const uint32_t sub = t % 36;
    n = t / 36, s = sub / 12, kh = (sub / 6) & 1, k = sub % 6 * 32 + lane;
  }
};
constexpr int WTASK = 24 * 64;
__device__ __forceinline__ void prep_load(uint32_t dst, const __nv_bfloat16* __restrict__ w, uint32_t t, int lane) {
  const Task q(min(t, NTASK - 1), 0);
  w += ((q.s * 24 + 2 * q.n + q.kh) * 8 + (lane >> 2)) * CH + q.k + (lane & 3) * 8;
#pragma unroll
  for (int r = 0; r < 3; r++)
    asm volatile("cp.async.cg.shared.global [%0], [%1], 16;" ::"r"(dst + r * 512 + lane * 16), "l"(w + r * 3 * CH * CH) : "memory");
}
__device__ __forceinline__ void prep_store(const float (&g)[3][8], bool tiny, uint4* u, uint32_t t, bool h, int lane) {
  const Task q(t, lane);
  const uint32_t n = q.n, s = q.s, kh = q.kh, k = q.k;
  const uint32_t jn = (k >> 5) * 4 + ((k >> 1) & 3), row = ((k >> 3) & 3) * 2 + (k & 1);
  u += (((h ? 4 * NSUB : 0) + n) * USLAB + s * UTILE + jn * 256 + kh * 128 + row * 16) >> 4;
  constexpr float nA = -1.f / (2.f * A2 * DD), nB = 1.f / (2.f * B2 * DD);
  constexpr float f0 = nA / S1, f1 = nA / S2, f2 = nB / S3, f3 = nB / S4, f4 = 1.f / (A2 * B2);
  const float co[4][3] = {{h ? f4 : f0, h ? 0.f : PA * f0, h ? 0.f : A2 * f0},
                          {h ? 0.f : f1, h ? 0.f : -PA * f1, h ? 1.f : A2 * f1},
                          {f2, PB * f2, B2 * f2},
                          {f3, -PB * f3, B2 * f3}};
#pragma unroll
  for (int p = 0; p < 4; p++) {
    if (p == 2 && h) break;
    uint32_t o[4];
#pragma unroll
    for (int e = 0; e < 4; e++) {
      float v[2];
#pragma unroll
      for (int q = 0; q < 2; q++) v[q] = co[p][0] * g[0][2 * e + q] + co[p][1] * g[1][2 * e + q] + co[p][2] * g[2][2 * e + q];
      const uint32_t b = pack_bf16(v[0], v[1]);
      o[e] = pack_f16(__uint_as_float(b << 16), __uint_as_float(b & 0xFFFF0000u));
    }
    constexpr uint32_t lim = U_LIM * 0x10001u;
    if (__vimax3_u16x2(__vimax3_u16x2(lim, o[0] & NAN2, o[1] & NAN2), o[2] & NAN2, o[3] & NAN2) != lim || tiny) o[0] = NAN2;
    u[p * NSUB * USLAB / 16] = make_uint4(o[0], o[1], o[2], o[3]);
  }
}

constexpr int ROWB = IMG * CH * 2;

__device__ __forceinline__ int region_px(int r) { return (r >> 3) * 8 * IMG + (r & 7) * 64; }
__device__ __forceinline__ int halo_x(int r) { return (r & 7) * 64 - 1; }
__device__ __forceinline__ int halo_y(int r) { return (r >> 3) * 8 - 1; }

__device__ __noinline__ void direct_patch(const __nv_bfloat16* __restrict__ x, const __nv_bfloat16* __restrict__ w,
                                          __nv_bfloat16* __restrict__ out, int y0, int x0, int lane) {
  const int g = lane >> 2, t = lane & 3;
#pragma unroll 1
  for (int k0 = 0; k0 < CH; k0 += 48) {
    float acc[4][6][4] = {};
#pragma unroll 1
    for (int rs = 0; rs < 9; rs++) {
      const int iy = y0 + rs / 3 - 1, ix = x0 + rs % 3 - 1 + g;
#pragma unroll 2
      for (int c = 4 * t; c < CH; c += 16) {
        uint32_t b[6][2];
#pragma unroll
        for (int m = 0; m < 6; m++) {
          const uint32_t* p = (const uint32_t*)(w + (rs * CH + c + (m & 1) * 2) * CH + k0 + (m >> 1) * 16 + 2 * g);
          const uint32_t lo = p[0], hi = p[CH / 2];
          b[m & 6][m & 1] = __byte_perm(lo, hi, 0x5410);
          b[m | 1][m & 1] = __byte_perm(lo, hi, 0x7632);
        }
#pragma unroll
        for (int y = 0; y < 4; y++) {
          uint2 a[2];
#pragma unroll
          for (int h = 0; h < 2; h++)
            a[h] = (unsigned)(iy + y) < IMG && (unsigned)(ix + 8 * h) < IMG ? *(const uint2*)(x + ((iy + y) * IMG + ix + 8 * h) * CH + c)
                                                                           : make_uint2(0, 0);
#pragma unroll
          for (int m = 0; m < 6; m++)
            asm("mma.sync.aligned.m16n8k16.row.col.f32.bf16.bf16.f32 {%0,%1,%2,%3}, {%4,%5,%6,%7}, {%8,%9}, {%0,%1,%2,%3};"
                : "+f"(acc[y][m][0]), "+f"(acc[y][m][1]), "+f"(acc[y][m][2]), "+f"(acc[y][m][3])
                : "r"(a[0].x), "r"(a[1].x), "r"(a[0].y), "r"(a[1].y), "r"(b[m][0]), "r"(b[m][1]));
        }
      }
    }
#pragma unroll
    for (int y = 0; y < 4; y++)
#pragma unroll
      for (int m = 0; m < 6; m += 2)
#pragma unroll
        for (int h = 0; h < 2; h++)
          *(uint2*)(out + ((y0 + y) * IMG + x0 + g + 8 * h) * CH + k0 + m * 8 + 4 * t) =
              make_uint2(pack_bf16(acc[y][m][2 * h], acc[y][m + 1][2 * h]), pack_bf16(acc[y][m][2 * h + 1], acc[y][m + 1][2 * h + 1]));
  }
}

struct Descs { uint64_t a[2][6], b[22]; };
__host__ __device__ constexpr int slot_use(int i) {
  int c = 0;
  for (int j = 0; j < i; j++) c += vslot(step_p(j), step_n(j)) == vslot(step_p(i), step_n(i));
  return c;
}

__host__ __device__ constexpr int out_time(int q) {
  constexpr int t[24] = {
      49, 50, 51, 52, 54, 55, 56, 57, 59, 60, 61, 63, 64, 65, 66, 68, 69, 70, 72, 74, 76, 78, 80, 82};
  return t[q];
}
__host__ __device__ constexpr int out_at(int t) {
  for (int q = 0; q < 24; q++)
    if (out_time(q) % NSTEP == t) return q;
  return -1;
}
__host__ __device__ constexpr bool out_ok() {
  for (int q = 0; q < 24; q++)
    if (out_time(q) <= last_on(q / 6) || out_time(q) < PIV + (q < 12 ? 4 : 6) || out_time(q) >= first_on(q / 6) + NSTEP ||
        (q && out_time(q) <= out_time(q - 1)))
      return false;
  return true;
}
static_assert(out_ok(), "output plan");
constexpr int OUT_END = out_time(23) + 1 - NSTEP;

struct Consumer {
  uint32_t c1[48], c2[48], c3[48], c4[48];
  const uint64_t *descA, *descB;
  static constexpr uint32_t sb = SMEM_BASE;
  uint8_t* pout;
  int bid, nblk, nlong;
  uint32_t done;
  uint32_t osc, ymax[2];
  bool lead, ok, odd;

  uint32_t one;
  __device__ __forceinline__ bool always() {
    uint32_t v = one;
    asm volatile("" : "+r"(v));
    return v != 0;
  }
  __device__ __forceinline__ void axpy(uint32_t (&a)[48], uint32_t k, uint32_t (&b)[48]) {
    if (always()) {
      reg_fence(a); reg_fence(b);
#pragma unroll
      for (int i = 0; i < 48; i++) {
        a[i] = hfma2(k, b[i], a[i]);
        if (i % 12 == 11) {
          asm volatile("" : "+r"(a[i])::"memory");
          sched_barrier();
        }
      }
      reg_fence(a);
    }
  }
  uint32_t pa[4], pb[4], px[4];
  __device__ __forceinline__ uint32_t to_bf16(uint32_t h, uint32_t& m) {
    float lo, hi;
    asm("{\n.reg .b16 l, h;\n.reg .b32 m;\nmov.b32 {l, h}, %3;\ncvt.f32.f16 %0, l;\ncvt.f32.f16 %1, h;\n"
        "abs.f16x2 m, %3;\nmax.NaN.f16x2 %2, m, %2;\n}\n" : "=f"(lo), "=f"(hi), "+r"(m) : "r"(h));
    return bmul2(pack_bf16(lo, hi), osc);
  }
  template <int Q, int EXTRA>
  __device__ __forceinline__ void stg(const uint32_t (&v)[4]) {
    constexpr int y = Q < 6 ? 1 : Q < 12 ? 2 : Q < 18 ? 0 : 3;
    asm volatile("st.global.cs.v4.u32 [%0+%5], {%1,%2,%3,%4};" ::"l"(pout), "r"(v[0]), "r"(v[1]), "r"(v[2]), "r"(v[3]),
                 "n"(y * ROWB + (Q / 3) % 2 * 8 * (CH * 2) + Q % 3 * 128 + EXTRA) : "memory");
  }
  template <int Q, bool YIELD>
  __device__ __forceinline__ void convert(uint32_t (&a)[4], uint32_t (&b)[4], uint32_t (&send)[4]) {
    if constexpr (Q >= 0) {
      const uint32_t(&d)[48] = Q < 6 ? c1 : Q < 12 ? c2 : Q < 18 ? c3 : c4;
      constexpr int o = 16 * (Q % 3) + (Q / 3) % 2;
#pragma unroll
      for (int e = 0; e < 4; e++) {
        if (YIELD && e % 2 == 0) sched_barrier();
        a[e] = to_bf16(d[o + 2 * e], ymax[o & 1]);
        b[e] = to_bf16(d[o + 8 + 2 * e], ymax[o & 1]);
        send[e] = odd ? a[e] : b[e];
      }
    }
  }
  template <int QW, int QR, bool STEP>
  __device__ __forceinline__ void output() {
    uint32_t u[4], v[4], a[4], b[4], send[4];
    if constexpr (!STEP) convert<QR, false>(a, b, send);
    sched_barrier();
#pragma unroll
    for (int e = 0; e < 4; e++) {
      u[e] = odd ? px[e] : pa[e];
      v[e] = odd ? pb[e] : px[e];
    }
    if constexpr (STEP) {
      convert<QR, true>(a, b, send);
      asm volatile("{\n.reg .pred p;\nsetp.ne.u32 p, %0, 0;\n@p pmevent 0;\n}" ::"r"((uint32_t)ok) : "memory");
      sched_barrier();
    }
    if constexpr (QW >= 0 && STEP) { stg<QW, 0>(u); stg<QW, CH * 2>(v); }
    if constexpr (QR >= 0) {
#pragma unroll
      for (int e = 0; e < 4; e++) px[e] = __shfl_xor_sync(0xffffffffu, send[e], 4), pa[e] = a[e], pb[e] = b[e];
    }
    if constexpr (QW >= 0 && !STEP) { stg<QW, 0>(u); stg<QW, CH * 2>(v); }
    sched_barrier();
  }
  __device__ __forceinline__ void range_check() {
    sched_barrier();
    uint32_t m = __vmaxu2(__byte_perm(ymax[0], ymax[1], 0x5410), __byte_perm(ymax[0], ymax[1], 0x7632));
    m = __vmaxu2(m, __shfl_xor_sync(0xffffffffu, m, 1));
    m = __vmaxu2(m, __shfl_xor_sync(0xffffffffu, m, 2));
    asm volatile("{\n.reg .pred p;\nsetp.ge.u32 p, %2, %3;\n@p st.shared.u8 [%0], %1;\n}" ::"r"(sb + OFF_REDO + (threadIdx.x & ~31u) + done), "r"(1),
                 "r"(max((m & 0xFFFFu) - Y_MIN, (m >> 16) - Y_MIN)), "n"(Y_INF - Y_MIN) : "memory");
    ymax[0] = ymax[1] = 0;
  }
  template <int T, int Q0, int Q1, int Q = Q0>
  __device__ __forceinline__ void flush() {
    if constexpr (Q <= Q1) {
      constexpr int QW = Q > Q0 && out_time((Q + 23) % 24) >= T - 1 ? Q - 1 : -1, QR = Q < Q1 && out_time(Q % 24) >= T ? Q : -1;
      if constexpr (QW >= 0 || QR >= 0) output<QW, QR, false>();
      flush<T, Q0, Q1, Q + 1>();
    }
  }
  template <int I>
  __device__ __forceinline__ void hook() {
    constexpr float LP = PB * (PB - PA) / (2.f * A2), LM = PB * (PB + PA) / (2.f * A2);
    constexpr int QW = out_at((I + NSTEP - 1) % NSTEP), QR = out_at(I);
    if constexpr (QW >= 0 || QR >= 0) output<QW, QR, true>();
    if constexpr (I == 22) {
      static_assert(OUT_END < NHEAD, "pointer update");
      range_check();
      osc = lds32(sb + OFF_OSC);
      const int r = bid + done * nblk, d = region_px(r) - region_px(r - nblk);
      asm volatile("mad.wide.s32 %0, %1, 384, %0;" : "+l"(pout) : "r"(d));
    }
    if constexpr (I == NHEAD) { if (bid >= nlong && done == 0 && !(bid & 3)) spin_cycles(24500); }
    if constexpr (I == 42) { if (bid >= nlong && done == 0 && (bid & 3)) spin_cycles(28000); }
    if constexpr (I == PIV) axpy(c1, h2const(S3 * (B2 / A2) / S1), c3);
    if constexpr (I == PIV) axpy(c2, h2const(S3 * (B2 / A2) / S2), c3);
    if constexpr (I == PIV + 1) axpy(c4, h2const(-S3 / S4), c3);
    if constexpr (I == PIV + 1) axpy(c1, h2const(S4 * LP / S1), c4);
    if constexpr (I == PIV + 2) axpy(c2, h2const(S4 * LM / S2), c4);
    if constexpr (I == PIV + 2) axpy(c3, h2const(S4 * (-DD / A2)), c4);
    if constexpr (I == PIV + 3) { axpy(c1, h2const(-1.f / (2.f * PA)), c2); axpy(c2, h2const(PA), c1); }
    if constexpr (I == PIV + 4) axpy(c4, h2const(A2), c1);
    if constexpr (I == PIV + 5) axpy(c3, h2const(1.f / A2), c2);
  }

  template <int I, int END, bool FIRST = false>
  __device__ __forceinline__ void steps() {
    if constexpr (I < END) {
      constexpr int J = (I + 1) % NSTEP, S = FIRST ? head(I) : I, T = FIRST ? head(J) : J, G = FIRST ? head_gate_of(I) : gate_of(I);
      uint32_t(&d)[48] = step_acc(S) == 0 ? c1 : step_acc(S) == 1 ? c2 : step_acc(S) == 2 ? c3 : c4;
      constexpr int vo = vslot(step_p(S), step_n(S)) * VSLOT, uo = USLOT<I> * USLAB;
      if (!ok) {
        mbar_wait_short(sb + BAR_UFULL + 8 * USLOT<I>, UUSE<I> & 1);
        if constexpr (first_use(step_n(S)) == S) mbar_wait_short(sb + BAR_VFULL + 8 * (step_n(S) % NB), step_n(S) / NB);
      }
      const uint64_t da = descA[FIRST ? 4 : slot_use(I)], db = descB[(FIRST ? 16 : 0) + UUSE<I>];
      wg_fence();
      wgmma192<vo, uo>(d, da, db, first_on(step_acc(S)) == S ? 0u : 1u);
      wgmma192<vo + 16, uo + UTILE>(d, da, db, 1u);
      wgmma192<vo + 32, uo + 2 * UTILE>(d, da, db, 1u);
      wg_commit();
      ok = mbar_test(sb + BAR_UFULL + 8 * USLOT<J>, UUSE<J> & 1);
      if constexpr (first_use(step_n(T)) == T) ok &= mbar_test(sb + BAR_VFULL + 8 * (step_n(T) % NB), step_n(T) / NB);
      if constexpr (!FIRST) hook<I>();
      wg_wait<0>();
      reg_fence(d);
      if (lead) mbar_arrive(sb + BAR_UEMPTY + 8 * USLOT<I>);
      if constexpr (G >= 0) { if (lead) mbar_arrive(sb + BAR_GATE + 8 * (G % NB)); }
      steps<I + 1, END, FIRST>();
    }
  }
  template <int I>
  __device__ __forceinline__ void chain() {
    if constexpr (I < NSTEP) {
      static_assert(step_acc(I) == 3 && NSTEP - I <= NU, "chain");
      constexpr int vo = vslot(step_p(I), step_n(I)) * VSLOT, uo = USLOT<I> * USLAB;
      mbar_wait_short(sb + BAR_UFULL + 8 * USLOT<I>, UUSE<I> & 1);
      const uint64_t da = descA[5], db = descB[21];
      wg_fence();
      wgmma192<vo, uo>(c4, da, db, 1u);
      wgmma192<vo + 16, uo + UTILE>(c4, da, db, 1u);
      wgmma192<vo + 32, uo + 2 * UTILE>(c4, da, db, 1u);
      wg_commit();
      chain<I + 1>();
    }
  }
  template <int I>
  __device__ __forceinline__ void release() {
    if constexpr (I < NSTEP) {
      if (lead) mbar_arrive(sb + BAR_UEMPTY + 8 * USLOT<I>);
      release<I + 1>();
    }
  }
  template <int T>
  __device__ __forceinline__ void finish(bool second) {
    if (second) {
      flush<T, 0, 18>();
      asm volatile("bar.sync 1, 256;" ::: "memory");
    }
    chain<T>();
    if (!second) {
      asm volatile("bar.arrive 1, 256;" ::: "memory");
      flush<T, 0, 18>();
    }
    wg_wait<0>();
    reg_fence(c4);
    release<T>();
    done++;
    flush<T, 18, 24>();
  }
};

struct SlotTab { uint32_t off[NSUB][8]; };
constexpr SlotTab make_slots() {
  SlotTab t = {};
  for (int n = 0; n < NSUB; n++)
    for (int p = 0; p < 6; p++) t.off[n][p] = vslot(p, n) * VSLOT;
  return t;
}
__constant__ __align__(64) SlotTab c_slots = make_slots();

constexpr int PF_X = 22, PF_BYTES = PF_X * 2 * 16, PF_NB = 12, U_LEAD = 10;
static_assert(PF_BYTES + 64 <= OFF_U - OFF_SINK, "sink");
__host__ __device__ constexpr uint32_t pf_box(int k) { return 1u << 31 | (k / PF_NB / 3) << 30 | (k / PF_NB % 3) << 28 | (k % PF_NB) << 24; }
__host__ __device__ constexpr int slab_of(int i) { return step_p(i % NSTEP) * NSUB + step_n(i % NSTEP); }
struct LoadTab { uint32_t e[2 * NSTEP]; };
constexpr LoadTab make_loads() {
  LoadTab t = {};
  constexpr int win[6] = {25, 42, 45, 72, 73, 96};
  for (int k = 0, i = 0; k < 6 * PF_NB; k++) {
    const int g = k / PF_NB % 3, when = win[2 * g] + k % PF_NB * (win[2 * g + 1] - win[2 * g]) / PF_NB - (k < 3 * PF_NB ? NSTEP : 0);
    if (when >= 0 && when < NSTEP) t.e[NSTEP + when] = pf_box(k);
    if (k < PF_NB) continue;
    if (i < when) i = when;
    if (i < NSTEP) t.e[i++] = pf_box(k);
  }
  for (int i = 0; i < 2 * NSTEP; i++) {
    int d = 1;
    while (uslot((i + d) % NSTEP) != uslot(i % NSTEP)) d++;
    if (d > NU + 1) d = 0;
    t.e[i] |= (uuse(i % NSTEP) & 1) << 23 | uslot(i % NSTEP) << 20 | d << 16 | slab_of(i + U_LEAD) << 8 | slab_of(head(i + d));
  }
  return t;
}
__constant__ __align__(64) LoadTab c_load = make_loads();

template <int I>
__device__ __forceinline__ void first_slabs(const uint8_t* u) {
  if constexpr (utrigger(I) < 0) {
    constexpr int slab = slab_of(head(I));
    load_u_warp(SMEM_BASE + OFF_U + USLOT<I> * USLAB, u + slab * USLAB, SMEM_BASE + BAR_UFULL + 8 * USLOT<I>);
    first_slabs<I + 1>(u);
  }
}

template <int BYTES>
__device__ __forceinline__ uint32_t warm(const void* p, uint32_t zero) {
  uint32_t v = ~0u;
#pragma unroll
  for (int o = 0; o < BYTES; o += 64) v &= ((const uint32_t*)p)[o / 4 + zero];
  return v;
}

__global__ void __launch_bounds__(384, 1) __cluster_dims__(1, 1, 1)
conv_kernel(const __grid_constant__ CUtensorMap tmX, const __grid_constant__ CUtensorMap tmH, const __grid_constant__ CUtensorMap tmP,
            const __nv_bfloat16* __restrict__ xin, const __nv_bfloat16* __restrict__ wgt, __nv_bfloat16* __restrict__ out,
            uint4* ubuf, uint32_t* arrived, int nblk, int nlong, int nmax, const __grid_constant__ Descs desc) {
  extern __shared__ uint8_t smem_raw[];
  const int tid = threadIdx.x, lane = tid & 31, bid = blockIdx.x;
  const int pidx = bid - (nblk - NP);
  constexpr uint32_t sb = SMEM_BASE;
  uint32_t epoch = 0;
  if (tid < 256) {
    cluster_arrive_relaxed();
    if (pidx >= 0) {
      const uint32_t t0 = pidx * 8 + (tid >> 5), wsm = sb + OFF_V + (tid >> 5) * NROUND * WTASK;
      prep_load(wsm, wgt, t0, lane);
      const Sample ws = sample_w(wgt, lane);
      const float sw = __uint_as_float(max(253 - (int)sample_exp(ws), 0) << 23);
      const int klane = (lane & 6) * 4 + (lane >> 3) * 2 + (lane & 1);
      int stage = 0;
#pragma unroll 1
      for (int round = 0; round < 2 * NROUND; round++) {
        const int k = round < NROUND ? round : round - NROUND;
        asm volatile("cp.async.wait_all;" ::: "memory");
        __syncwarp();
        float g[3][8], gmax = 0.f;
#pragma unroll
        for (int i = 0; i < 24; i++) {
          uint16_t v;
          asm volatile("ld.shared.u16 %0, [%1];" : "=h"(v) : "r"(wsm + k * WTASK + i * 64 + klane * 2) : "memory");
          g[i / 8][i % 8] = __uint_as_float((uint32_t)v << 16);
        }
        if (round >= NROUND) {
#pragma unroll
          for (int i = 0; i < 24; i++) gmax = fmaxf(gmax, fabsf(g[i / 8][i % 8]));
          sched_barrier();
        }
#pragma unroll
        for (int i = 0; i < 24; i++) g[i / 8][i % 8] *= sw;
        if (t0 + k * 8 * NP < NTASK) prep_store(g, gmax > 0.f && gmax * sw < W_MIN, ubuf, t0 + k * 8 * NP, round >= NROUND, klane);
        if (round + 1 == stage_end(0) || round + 1 == stage_end(1) || round + 1 == stage_end(2)) {
          if (++stage == NSTAGE) {
            fence_async();
            asm volatile("ld.relaxed.gpu.global.u32 %0, [%1];" : "=r"(epoch) : "l"(arrived + 32 * NSTAGE) : "memory");
          }
          asm volatile("bar.sync 1, 256;" ::: "memory");
          if (tid == 0) asm volatile("red.release.gpu.global.add.u32 [%0], %1;" ::"l"(arrived + 32 * stage), "r"(pidx ? 1 : 0x80000001u - NP) : "memory");
          asm volatile("bar.sync 1, 256;" ::: "memory");
          if (stage == 1) {
#pragma unroll 1
            for (int j = 1; j < NROUND; j++) prep_load(wsm + j * WTASK, wgt, t0 + j * 8 * NP, lane);
          }
        }
      }
      if (tid < 32) asm volatile("bar.arrive 2, 64;" ::: "memory");
    } else if (tid < 32) {
      epoch = stage_enter(arrived, lane, 1);
      spin_until(now(), 2200);
    }
  }
  if (tid >= 352) {
    asm volatile("prefetch.tensormap [%0];" ::"l"(&tmX) : "memory");
    constexpr uint64_t twos = ((2ull << NU) - 1) << (BAR_UEMPTY - OFF_BAR) / 8 | ((1ull << 2 * NB) - 1) << (BAR_VFULL - OFF_BAR) / 8;
    constexpr uint64_t threes = ((1ull << NB) - 1) << (BAR_VFULL - OFF_BAR) / 8;
    if (lane == 0) {
#pragma unroll
      for (int i = 0; i < NBAR; i++) mbar_init(sb + OFF_BAR + 8 * i, 1 + ((twos >> i) & 1) + ((threes >> i) & 1));
      asm volatile("fence.mbarrier_init.release.cluster;" ::: "memory");
      fence_async();
    }
    __syncwarp();
    cluster_arrive_relaxed();
    epoch = stage_enter(arrived, lane, pidx ? 1 : 0x80000001u + NP - 2 * nblk);
    if (pidx >= 0) asm volatile("bar.sync 2, 64;" ::: "memory");
    const uint32_t t0 = now();
#pragma unroll 1
    for (int k = 0, box = 0; k < 9; k++, box = box < 6 ? box + 3 : box - 5) {
      if (pidx < 0) spin_until(t0, min(k, 7) * 410);
      tma_box_warp(sb + OFF_X + box * XBOX, k < 8 ? &tmX : &tmH, sb + BAR_XFULL + 8 * box, k < 8 ? XBOX : XHBOX, 0, halo_x(bid) + k * 8,
                   halo_y(bid));
      if (k == 0) asm volatile("prefetch.tensormap [%0];\nprefetch.tensormap [%1];" ::"l"(&tmH), "l"(&tmP) : "memory");
    }
  }
  if (smem_u32(smem_raw) != SMEM_BASE) __trap();
  const int warp = __shfl_sync(0xffffffffu, tid >> 5, 0);

  if (warp < 8) {
    const int wg = warp >> 2;
    if (warp == 7) {
      spin_until(now(), 1300);
      if ((warm<sizeof(SlotTab)>(&c_slots, tid >> 10) & warm<sizeof(LoadTab)>(&c_load, tid >> 10)) == ~0u) __trap();
    }
    cluster_wait();
    if (warp == 0) {
      stage_wait(arrived + 32, __shfl_sync(0xffffffffu, epoch, 0));
      first_slabs<0>((const uint8_t*)ubuf);
    }
    asm volatile("setmaxnreg.inc.sync.aligned.u32 224;");
    Consumer c;
#pragma unroll
    for (int i = 0; i < 48; i++) { c.c1[i] = 0; c.c2[i] = 0; c.c3[i] = 0; c.c4[i] = 0; }
#pragma unroll
    for (int e = 0; e < 4; e++) c.pa[e] = c.pb[e] = c.px[e] = 0;
    c.descA = desc.a[wg];
    c.descB = desc.b;
    c.lead = (tid & 127) == 0;
    c.one = __shfl_sync(0xffffffffu, nblk, 0);
    c.ok = false;
    c.bid = bid;
    c.nblk = nblk;
    c.nlong = nlong;
    c.odd = (lane >> 2) & 1;
    c.pout = (uint8_t*)out + (long long)(region_px(bid - nblk) + wg * 4 * IMG + (warp & 3) * 16 + (lane >> 3) * 2) * (CH * 2) + (lane & 7) * 16;
    c.done = c.osc = c.ymax[0] = c.ymax[1] = 0;
    asm volatile("st.shared.u8 [%0], %1;" ::"r"(sb + OFF_REDO + tid), "r"(0) : "memory");
    constexpr int ROT = 69;
    c.steps<0, NHEAD, true>();
    bool tail = false;
#pragma unroll 1
    do {
      wg_wait<0>();
      if (tail) {
        c.steps<ROT, NSTEP>();
        c.done++;
        c.steps<0, NHEAD>();
      }
      c.steps<NHEAD, ROT>();
      tail = c.always();
    } while (bid + (int)(c.done + 1) * nblk < NREG);
    c.finish<ROT>(wg);
    c.range_check();
    __syncwarp();
    uint32_t redo;
    asm volatile("ld.shared.u8 %0, [%1];" : "=r"(redo) : "r"(sb + OFF_REDO + tid) : "memory");
    redo = __ballot_sync(0xffffffffu, redo) >> 1;
    if (redo) {
      for (int i = 0; i < (int)c.done; i++)
        if ((redo >> i) & 1) {
          const int r = bid + i * nblk;
          direct_patch(xin, wgt, out, (r >> 3) * 8 + wg * 4, (r & 7) * 64 + (warp & 3) * 16, lane);
        }
    }
  } else {
    asm volatile("setmaxnreg.dec.sync.aligned.u32 56;");
    const int nitem = nmax - (bid >= nlong);
    if (warp == 11) {
      const uint8_t* ubase = (const uint8_t*)ubuf;
      epoch = __shfl_sync(0xffffffffu, epoch, 0);
      cluster_wait();
      const uint8_t* uline = ubase + (bid * 2 + lane) * 128;
      const bool ufetch = lane < 2 && bid < USLAB / 256;
      int r = bid, npf = 0;
      int i = 0, tab = 0;
#pragma unroll 1
      for (int left = nitem * NSTEP - 1; left >= 0; left--) {
        const uint32_t e = c_load.e[tab + i], slot = (e >> 20) & 7;
        const uint8_t* src = ubase + (e & 255) * USLAB;
        const uint8_t* pu = uline + ((e >> 8) & 255) * USLAB;
        const uint32_t dst = sb + OFF_U + slot * USLAB, ebar = sb + BAR_UEMPTY + 8 * slot;
        const bool refill = ((e >> 16) & 7) - 1 < (uint32_t)left;
        constexpr int need1 = utrigger(stage_first(1)), need2 = utrigger(stage_first(2)), xslab = slab_of(UX_FIRST);
        if (tab + i == need1 || tab + i == need2) stage_wait(arrived + (i == need1 ? 64 : 96), epoch);
        refill_u(ebar, (e >> 23) & 1, refill, dst, src);
        if (i == UX_GATE) load_u_warp(sb + OFF_V, ubase + xslab * USLAB, sb + BAR_UFULL + 8 * NU);
        const int rr = r + ((e >> 30) & 1) * nblk;
        if ((int)e < 0 && rr < NREG) {
          asm volatile("{\n.reg .pred p;\nelect.sync _|p, 0xffffffff;\n"
                       "@p cp.async.bulk.tensor.3d.shared::cluster.global.mbarrier::complete_tx::bytes [%0], [%1, {%3, %4, %5}], [%2];\n}\n"
                       ::"r"(sb + OFF_SINK), "l"(&tmP), "r"(sb + BAR_SINK), "r"((e >> 22) & 0xC0), "r"(halo_x(rr) + ((e >> 26) & 3) * PF_X),
                       "r"(halo_y(rr) + 1 + ((e >> 23) & 6)) : "memory");
          npf++;
        }
        if (ufetch && tab + i >= NSTEP - U_LEAD && left >= U_LEAD)
          asm volatile("cp.async.ca.shared.global.L2::128B [%0], [%1], 4;" ::"r"(sb + OFF_SINK + PF_BYTES + lane * 4), "l"(pu) : "memory");
        if (++i == NSTEP) { i = 0; r += nblk; tab = NSTEP; }
      }
      if (lane == 0) asm volatile("mbarrier.arrive.expect_tx.shared::cta.b64 _, [%0], %1;" ::"r"(sb + BAR_SINK), "r"(npf * PF_BYTES) : "memory");
      mbar_wait(sb + BAR_SINK, 0);
      asm volatile("cp.async.wait_all;" ::: "memory");
    } else {
      cluster_arrive_relaxed();
      const int w = warp - 8, col = (lane >> 1) & 7, chunk = lane >> 4;
      const uint32_t xbox = sb + OFF_X + w * 3 * XBOX, xbar = sb + BAR_XFULL + 24 * w;
      const uint32_t xl = xbox + col * 32 + ((chunk ^ (col >> 2)) << 4) + (lane & 1) * 8;
      const uint32_t vl = sb + OFF_V + chunk * VROW + w * 128 + (lane & 15) * 8;
      const bool in_row = w < 2 || col < 2;
      const uint32_t pitch2 = w < 2 ? 256 : 64, bytes2 = 10 * pitch2;
      const uint32_t xl2 = w < 2 ? xl + 2 * XBOX : xbox + 2 * XBOX + col * 32 + chunk * 16 + (lane & 1) * 8;
      const CUtensorMap* tm2 = w < 2 ? &tmX : &tmH;
      auto xrow = [&](int j, int i) {
        uint2 v = make_uint2(0, 0);
        if (j < 2 || in_row) v = lds64(j < 2 ? xl + j * XBOX + i * 256 : xl2 + i * pitch2);
        return v;
      };
      const Sample ws = sample_w(wgt, lane), xs = sample_x(xin, bid, lane);
      uint32_t xsc;
      {
        const int ex = sample_exp(xs), eo = ex + (int)sample_exp(ws) - (111 + X_EXP), es = 127 + X_EXP - ex;
        xsc = es >= 1 && eo >= 1 && eo <= 254 ? es * 0x00800080u : NAN2;
        asm volatile("st.shared.u32 [%0], %1;" ::"r"(sb + OFF_OSC), "r"(eo * 0x00800080u) : "memory");
      }
      constexpr uint32_t gate_par = [] { uint32_t m = 0; for (int n = 0; n < NSUB; n++) if ((n / NB) ^ (gate(n % NB) < 0)) m |= 1u << n; return m; }();
      constexpr uint32_t LIM2 = X_LIM * 0x10001u;
      cluster_wait();
      auto conv = [&](uint2& v, uint32_t m) {
        const uint32_t tx = bmul2(v.x, xsc), ty = bmul2(v.y, xsc), ux = tx & NAN2, uy = ty & NAN2;
        v = make_uint2(ux * 7 + tx, uy * 7 + ty);
        return __vimax3_u16x2(m, ux, uy);
      };
      uint32_t so[6] = {};
      auto planes = [&](const uint2* h, uint32_t m, uint32_t a, bool on) {
        constexpr uint32_t NB2 = h2const(-B2), NA2 = h2const(-A2);
        const uint2 e1 = fma4(NB2, h[2], h[4]), e2 = fma4(NA2, h[2], h[4]);
        store_v(a + so[4], fma4(NA2, fma4(NB2, h[0], h[2]), e1), on);
        const uint2 o1 = fma4(NB2, h[1], h[3]), o2 = fma4(NA2, h[1], h[3]);
        store_v(a + so[5], fma4(NA2, o1, fma4(NB2, h[3], h[5])), on);
        uint2 v = fma4(h2const(PA), o1, e1);
        if (m != LIM2) v.x = NAN2;
        store_v(a + so[0], v, on);
        store_v(a + so[1], fma4(h2const(-PA), o1, e1), on);
        store_v(a + so[2], fma4(h2const(PB), o2, e2), on);
        store_v(a + so[3], fma4(h2const(-PB), o2, e2), on);
      };
      int r = bid, n = 0;
      uint32_t par = 0;
#pragma unroll 1
      for (int left = nitem * NSUB; left > 0; left--) {
        const int nb = n >= NB ? n - NB : n;
        uint2 d[10];
        mbar_wait(xbar, par);
#pragma unroll
        for (int i = 0; i < 6; i++) d[i] = xrow(0, i);
#pragma unroll
        for (int p = 0; p < 6; p++) so[p] = c_slots.off[n][p];
        const uint32_t gpar = (gate_par >> n) & 1;
        if (++n == NSUB) { n = 0; r += nblk; }
        const int fc = n * 16, fx = halo_x(r) + w * 8, fy = halo_y(r);
#pragma unroll
        for (int j = 0; j < 3; j++) {
          const bool on = j < 2 || in_row;
#pragma unroll
          for (int i = 6; i < 10; i++) d[i] = xrow(j, i);
          const bool xok = j < 2 && mbar_test(xbar + 8 * (j + 1), par);
          sched_barrier();
          const uint32_t m45 = conv(d[5], conv(d[4], LIM2));
          const uint32_t ma = conv(d[3], conv(d[1], conv(d[0], conv(d[2], m45))));
          if (j == 0) mbar_wait(sb + BAR_GATE + 8 * nb, gpar);
          planes(d, ma, vl + j * 384, on);
          sched_barrier();
          const uint32_t mb = conv(d[9], conv(d[7], conv(d[6], conv(d[8], m45))));
          if (left > 1) tma_box_warp(xbox + j * XBOX, j < 2 ? &tmX : tm2, xbar + 8 * j, (j < 2 ? XBOX : bytes2) | (mb & 0x8000u), fc, fx + j * 24, fy);
          uint2 h[6];
#pragma unroll
          for (int i = 0; i < 6; i++) h[i] = d[4 + i];
          if (j < 2) {
            mbar_wait(xbar + 8 * (j + 1), par, xok);
#pragma unroll
            for (int i = 0; i < 6; i++) d[i] = xrow(j + 1, i);
          }
          sched_barrier();
          planes(h, mb, vl + j * 384 + VPIECE, on);
          sched_barrier();
        }
        fence_async();
        asm volatile("{\n.reg .pred p;\nelect.sync _|p, 0xffffffff;\n@p mbarrier.arrive.shared::cta.b64 _, [%0];\n}\n" ::"r"(sb + BAR_VFULL + 8 * nb) : "memory");
        par ^= 1;
      }
    }
  }
}

constexpr uint64_t make_desc(uint32_t off, uint32_t lbo, uint32_t sbo) {
  return (uint64_t)((SMEM_BASE + off) >> 4) | ((uint64_t)(lbo >> 4) << 16) | ((uint64_t)(sbo >> 4) << 32);
}

typedef CUresult (*EncodeFn)(CUtensorMap*, CUtensorMapDataType, cuuint32_t, void*, const cuuint64_t*, const cuuint64_t*,
                             const cuuint32_t*, const cuuint32_t*, CUtensorMapInterleave, CUtensorMapSwizzle,
                             CUtensorMapL2promotion, CUtensorMapFloatOOBfill);

}

extern "C" void kernel_launch(void* const* d_in, const int* in_sizes, int n_in, void* d_out, int out_size) {
  static EncodeFn enc = nullptr;
  static int nblk = 0;
  static uint4* ubuf;
  static uint32_t* arrived;
  if (!enc) {
    cudaGetSymbolAddress((void**)&ubuf, g_U);
    cudaGetSymbolAddress((void**)&arrived, g_arrived);
    cudaDriverEntryPointQueryResult qr;
    cudaGetDriverEntryPoint("cuTensorMapEncodeTiled", (void**)&enc, cudaEnableDefault, &qr);
    cudaFuncSetAttribute(conv_kernel, cudaFuncAttributeMaxDynamicSharedMemorySize, SMEM_BYTES);
    int dev;
    cudaGetDevice(&dev);
    cudaDeviceGetAttribute(&nblk, cudaDevAttrMultiProcessorCount, dev);
  }
  CUtensorMap tmX, tmH, tmP;
  const cuuint64_t dims[3] = {CH, IMG, IMG};
  const cuuint64_t strides[2] = {CH * 2, (cuuint64_t)CH * 2 * IMG};
  const cuuint32_t es[3] = {1, 1, 1};
  const cuuint32_t boxX[3] = {16, 8, 10}, boxH[3] = {16, 2, 10}, boxP[3] = {8, PF_X, 2};
  enc(&tmH, CU_TENSOR_MAP_DATA_TYPE_BFLOAT16, 3, d_in[0], dims, strides, boxH, es, CU_TENSOR_MAP_INTERLEAVE_NONE,
      CU_TENSOR_MAP_SWIZZLE_NONE, CU_TENSOR_MAP_L2_PROMOTION_L2_64B, CU_TENSOR_MAP_FLOAT_OOB_FILL_NONE);
  enc(&tmP, CU_TENSOR_MAP_DATA_TYPE_BFLOAT16, 3, d_in[0], dims, strides, boxP, es, CU_TENSOR_MAP_INTERLEAVE_NONE,
      CU_TENSOR_MAP_SWIZZLE_NONE, CU_TENSOR_MAP_L2_PROMOTION_L2_128B, CU_TENSOR_MAP_FLOAT_OOB_FILL_NONE);
  enc(&tmX, CU_TENSOR_MAP_DATA_TYPE_BFLOAT16, 3, d_in[0], dims, strides, boxX, es, CU_TENSOR_MAP_INTERLEAVE_NONE,
      CU_TENSOR_MAP_SWIZZLE_32B, CU_TENSOR_MAP_L2_PROMOTION_L2_64B, CU_TENSOR_MAP_FLOAT_OOB_FILL_NONE);
  Descs desc = {};
  for (int i = 0; i < 6; i++) { desc.a[0][i] = make_desc(OFF_V, VROW, 128); desc.a[1][i] = make_desc(OFF_V + VPIECE, VROW, 128); }
  for (int i = 0; i < 22; i++) desc.b[i] = make_desc(OFF_U, 128, 256);
  conv_kernel<<<nblk, 384, SMEM_BYTES>>>(tmX, tmH, tmP, (const __nv_bfloat16*)d_in[0], (const __nv_bfloat16*)d_in[1], (__nv_bfloat16*)d_out, ubuf, arrived, nblk,
                                         NREG % nblk ? NREG % nblk : nblk, (NREG + nblk - 1) / nblk, desc);
}
```

```cpp
#include <cuda_runtime.h>
#include <cuda_bf16.h>
#include <cuda.h>
#include <stdint.h>

namespace {

constexpr int IMG = 512, CH = 192;
constexpr float PA = 1.5f, PB = 0.6875f;
constexpr float A2 = PA * PA, B2 = PB * PB, DD = B2 - A2;

constexpr int NSTEP = 72, NSUB = 12;
__host__ __device__ constexpr int sched(int i) {
  constexpr int t[NSTEP] = {
      0x00, 0x10, 0x20, 0x01, 0x11, 0x21, 0x02, 0x12, 0x22, 0x03, 0x13, 0x23, 0x30, 0x31, 0x32, 0x33, 0x24, 0x34,
      0x04, 0x14, 0x25, 0x35, 0x05, 0x15, 0x26, 0x36, 0x06, 0x16, 0x27, 0x37, 0x07, 0x17, 0x28, 0x38, 0x08, 0x18,
      0x29, 0x39, 0x09, 0x19, 0x2a, 0x3a, 0x0a, 0x1a, 0x2b, 0x3b, 0x1b, 0x0b, 0x40, 0x4b, 0x50, 0x41, 0x51, 0x4a,
      0x49, 0x48, 0x47, 0x42, 0x52, 0x46, 0x45, 0x5b, 0x44, 0x43, 0x5a, 0x53, 0x59, 0x58, 0x57, 0x56, 0x54, 0x55};
  return t[i];
}
__host__ __device__ constexpr int step_p(int i) { return sched(i) >> 4; }
__host__ __device__ constexpr int step_n(int i) { return sched(i) & 15; }
__host__ __device__ constexpr int step_acc(int i) { return step_p(i) < 4 ? step_p(i) : step_p(i) - 2; }
__host__ __device__ constexpr int first_on(int acc) {
  for (int i = 0; i < NSTEP; i++)
    if (step_acc(i) == acc) return i;
  return -1;
}
__host__ __device__ constexpr int last_on(int acc) {
  for (int i = NSTEP - 1; i >= 0; i--)
    if (step_acc(i) == acc) return i;
  return -1;
}
__host__ __device__ constexpr int find_step(int p, int n) {
  for (int i = 0; i < NSTEP; i++)
    if (sched(i) == p * 16 + n) return i;
  return -1;
}
__host__ __device__ constexpr int first_use(int n) {
  for (int i = 0; i < NSTEP; i++)
    if (step_n(i) == n) return i;
  return -1;
}
constexpr int NHEAD = first_on(3) / 3 * 4;
__host__ __device__ constexpr int head(int i) { return i < NHEAD ? find_step(i % 4, i / 4) : i; }
constexpr float S1 = 1.f / PA, S2 = 1.f / (2.f * A2), S3 = -A2 / (2.f * DD), S4 = -1.f / (PB * DD);
constexpr int PIV = find_step(3, NSUB - 1);
static_assert(find_step(2, NSUB - 1) == PIV - 1 && last_on(1) == PIV + 1 && last_on(0) == PIV + 2 && PIV + 3 == 4 * NSUB &&
              step_p(PIV + 3) == 4 && step_p(PIV + 4) == 4 && step_p(PIV + 5) == 5, "basis change");

constexpr int NV = 32, NB = 6;
__host__ __device__ constexpr int vslot(int p, int n) {
  constexpr int t[6][NSUB] = {
      {31, 19, 25, 18, 19, 27, 21, 4, 24, 26, 3, 26}, {28, 23, 24, 22, 17, 24, 28, 3, 25, 27, 0, 28},
      {27, 17, 14, 20, 23, 22, 20, 31, 0, 28, 1, 2}, {26, 21, 15, 16, 31, 18, 23, 26, 23, 31, 4, 31},
      {7, 6, 8, 10, 12, 14, 15, 17, 19, 21, 23, 27}, {30, 29, 9, 11, 13, 5, 16, 18, 20, 22, 24, 25}};
  return t[p][n];
}
__host__ __device__ constexpr int gate(int n) {
  constexpr int t[NSUB] = {-20, -14, -8, -2, 5, 11, 16, 21, 25, 29, 34, 39};
  return t[n];
}
__host__ __device__ constexpr int gate_of(int i) {
  for (int n = 0; n < NSUB; n++)
    if ((gate(n) + NSTEP) % NSTEP == i) return n;
  return -1;
}
__host__ __device__ constexpr int head_gate_of(int i) {
  for (int n = 0; n < NSUB; n++) {
    int m = -1;
    for (int j = 0; j < NHEAD; j++)
      if (head(j) <= gate(n)) m = j;
    if (gate(n) < NHEAD && m == i) return n;
  }
  return -1;
}
__host__ __device__ constexpr bool gates_ok() {
  int early = 0;
  for (int i = 0; i < NHEAD; i++) early += (gate_of(i) >= 0) - (head_gate_of(i) >= 0) + (head(i) >= NHEAD);
  if (early) return false;
  for (int n = 0; n < NSUB; n++) {
    for (int p = 0; p < 6; p++)
      for (int d = 1; d <= NSUB; d++)
        for (int q = 0; q < 6; q++) {
          const int m = (n - d + NSUB) % NSUB;
          if (vslot(q, m) == vslot(p, n) && (find_step(q, m) - (n - d < 0 ? NSTEP : 0) > gate(n) || (m == n && p != q))) return false;
        }
    if (n > 0 && (gate(n) <= gate(n - 1) || first_use(n) <= first_use(n - 1))) return false;
    if (gate(n) >= first_use(n)) return false;
    if (gate((n + NB) % NSUB) + (n >= NB ? NSTEP : 0) < first_use(n)) return false;
  }
  return gate(0) + NSTEP > gate(NSUB - 1) && gate(NB) >= 0;
}
static_assert(gates_ok(), "gates");

constexpr int UTILE = CH * 16 * 2;
constexpr int USLAB = 3 * UTILE;
constexpr int NU = 4;
constexpr int VROW = 66 * 16;
constexpr int VPIECE = 2 * VROW;
constexpr int VSLOT = 2 * VPIECE;
constexpr int XBOX = 10 * 8 * 32;
constexpr int XHBOX = 10 * 2 * 32;
constexpr int UX_FIRST = 52, UX_COUNT = 8, UX_GATE = UX_FIRST - NU - 1;
__host__ __device__ constexpr bool uextra(int i) {
  const int d = (i - UX_FIRST + NSTEP) % NSTEP;
  return d % (NU + 1) == 0 && d / (NU + 1) < UX_COUNT;
}
__host__ __device__ constexpr int uindex(int i) {
  int c = 0;
  for (int j = 0; j < i; j++) c += uextra(j) == uextra(i);
  return c;
}
__host__ __device__ constexpr int uslot(int i) { return uextra(i) ? NU : uindex(i) % NU; }
__host__ __device__ constexpr int uuse(int i) { return uextra(i) ? uindex(i) : uindex(i) / NU; }
__host__ __device__ constexpr int utrigger(int j) {
  if (j == UX_FIRST) return UX_GATE;
  int i = j - 1;
  while (uslot((i + NSTEP) % NSTEP) != uslot(j)) i--;
  return i;
}
template <int I> constexpr int USLOT = uslot(I);
template <int I> constexpr int UUSE = uuse(I);
__host__ __device__ constexpr bool uring_ok() {
  for (int n = 0; n < NSUB; n++)
    for (int p = 0; p < 6; p++)
      if (vslot(p, n) * VSLOT < USLAB && (find_step(p, n) > UX_GATE || gate(n) < UX_FIRST + (NU + 1) * (UX_COUNT - 1) - NSTEP))
        return false;
  return UX_COUNT % 2 == 0 && (NSTEP - UX_COUNT) % (2 * NU) == 0;
}
static_assert(uring_ok(), "U ring");

constexpr int OFF_X = 0;
constexpr int OFF_SINK = OFF_X + 8 * XBOX + XHBOX;
constexpr int OFF_U = OFF_SINK + 768;
constexpr int OFF_V = OFF_U + NU * USLAB;
constexpr int OFF_BAR = OFF_V + NV * VSLOT;
constexpr int BAR_UFULL = OFF_BAR;
constexpr int BAR_UEMPTY = BAR_UFULL + 8 * (NU + 1);
constexpr int BAR_XFULL = BAR_UEMPTY + 8 * (NU + 1);
constexpr int BAR_VFULL = BAR_XFULL + 8 * 9;
constexpr int BAR_GATE = BAR_VFULL + 8 * NB;
constexpr int BAR_SINK = BAR_GATE + 8 * NB;
constexpr int OFF_OSC = BAR_SINK + 8;
constexpr int NBAR = (OFF_OSC - OFF_BAR) / 8;
constexpr int OFF_REDO = OFF_OSC + 8;
constexpr int SMEM_BYTES = OFF_REDO + 256;
constexpr uint32_t SMEM_BASE = 1024;
static_assert(SMEM_BYTES <= 232448, "smem");

constexpr int NREG = 512;

__device__ __align__(128) uint4 g_U[NSTEP * USLAB / 16];
__device__ uint32_t g_arrived[4 * 32];

__device__ __forceinline__ uint32_t smem_u32(const void* p) { return (uint32_t)__cvta_generic_to_shared(p); }
__device__ __forceinline__ void mbar_init(uint32_t a, int c) {
  asm volatile("mbarrier.init.shared::cta.b64 [%0], %1;" ::"r"(a), "r"(c) : "memory");
}
__device__ __forceinline__ void mbar_arrive(uint32_t a) {
  asm volatile("mbarrier.arrive.shared::cta.b64 _, [%0];" ::"r"(a) : "memory");
}
__device__ __forceinline__ void mbar_wait(uint32_t a, uint32_t parity, uint32_t skip = 0) {
  asm volatile(
      "{\n"
      ".reg .pred p;\n"
      ".reg .u32 n;\n"
      "setp.ne.u32 p, %2, 0;\n"
      "@p bra.uni LAB_DONE;\n"
      "mov.u32 n, 0;\n"
      "LAB_WAIT:\n"
      "mbarrier.try_wait.parity.shared::cta.b64 p, [%0], %1;\n"
      "@p bra.uni LAB_DONE;\n"
      "add.u32 n, n, 1;\n"
      "setp.lt.u32 p, n, 4000000;\n"
      "@p bra.uni LAB_WAIT;\n"
      "trap;\n"
      "LAB_DONE:\n"
      "}\n" ::"r"(a), "r"(parity), "r"(skip) : "memory");
}
__device__ __forceinline__ void mbar_wait_short(uint32_t a, uint32_t parity) {
  asm volatile("{\n.reg .pred p;\nLAB_WAIT:\nmbarrier.try_wait.parity.shared::cta.b64 p, [%0], %1;\n@!p bra.uni LAB_WAIT;\n}\n" ::"r"(a),
               "r"(parity) : "memory");
}
__device__ __forceinline__ bool mbar_test(uint32_t a, uint32_t parity) {
  uint32_t ok;
  asm volatile("{\n.reg .pred p;\nmbarrier.test_wait.parity.shared::cta.b64 p, [%1], %2;\nselp.u32 %0, 1, 0, p;\n}\n"
               : "=r"(ok) : "r"(a), "r"(parity) : "memory");
  return ok;
}
__device__ __forceinline__ void fence_async() { asm volatile("fence.proxy.async.shared::cta;" ::: "memory"); }
__device__ __forceinline__ void tma_box_warp(uint32_t dst, const CUtensorMap* tm, uint32_t bar, uint32_t bytes, int c, int x, int y) {
  asm volatile(
      "{\n.reg .pred p;\nelect.sync _|p, 0xffffffff;\n"
      "@p mbarrier.arrive.expect_tx.shared::cta.b64 _, [%2], %6;\n"
      "@p cp.async.bulk.tensor.3d.shared::cluster.global.mbarrier::complete_tx::bytes [%0], [%1, {%3, %4, %5}], [%2];\n}\n" ::"r"(dst),
      "l"(tm), "r"(bar), "r"(c), "r"(x), "r"(y), "r"(bytes) : "memory");
}
__device__ __forceinline__ void load_u_warp(uint32_t dst, const void* src, uint32_t bar) {
  asm volatile("{\n.reg .pred p;\nelect.sync _|p, 0xffffffff;\n"
               "@p mbarrier.arrive.expect_tx.shared::cta.b64 _, [%2], %3;\n"
               "@p cp.async.bulk.shared::cluster.global.mbarrier::complete_tx::bytes [%0], [%1], %3, [%2];\n}\n" ::"r"(dst),
               "l"(src), "r"(bar), "n"(USLAB) : "memory");
}
__device__ __forceinline__ void refill_u(uint32_t ebar, uint32_t parity, uint32_t on, uint32_t dst, const void* src) {
  asm volatile(
      "{\n.reg .pred p;\n.reg .u32 n;\n"
      "mov.u32 n, 0;\n"
      "LAB_WAIT:\n"
      "mbarrier.try_wait.parity.shared::cta.b64 p, [%0], %1;\n"
      "@p bra.uni LAB_DONE;\n"
      "add.u32 n, n, 1;\nsetp.lt.u32 p, n, 4000000;\n"
      "@p bra.uni LAB_WAIT;\n"
      "trap;\n"
      "LAB_DONE:\n"
      "setp.eq.u32 p, %2, 0;\n"
      "@p bra.uni LAB_OUT;\n"
      "elect.sync _|p, 0xffffffff;\n"
      "@p mbarrier.arrive.expect_tx.shared::cta.b64 _, [%5], %6;\n"
      "@p cp.async.bulk.shared::cluster.global.mbarrier::complete_tx::bytes [%3], [%4], %6, [%5];\n"
      "LAB_OUT:\n}\n" ::"r"(ebar), "r"(parity), "r"(on), "r"(dst), "l"(src), "r"(ebar - (BAR_UEMPTY - BAR_UFULL)), "n"(USLAB) : "memory");
}
__device__ __forceinline__ uint2 lds64(uint32_t a) {
  uint2 v;
  asm volatile("ld.shared.v2.u32 {%0,%1}, [%2];" : "=r"(v.x), "=r"(v.y) : "r"(a) : "memory");
  return v;
}
__device__ __forceinline__ uint32_t lds32(uint32_t a) {
  uint32_t v;
  asm volatile("ld.shared.u32 %0, [%1];" : "=r"(v) : "r"(a) : "memory");
  return v;
}
__device__ __forceinline__ void store_v(uint32_t a, uint2 v, bool on) {
  v.x &= 0xFFFCFFFCu; v.y &= 0xFFFCFFFCu;
  if (on) asm volatile("st.shared.v2.u32 [%0], {%1,%2};" ::"r"(a), "r"(v.x), "r"(v.y) : "memory");
}
__device__ __forceinline__ void sched_barrier() { asm volatile("pmevent 0;" ::: "memory"); }
__device__ __forceinline__ void spin_cycles(uint32_t n) {
  asm volatile(
      "{\n.reg .pred p;\n.reg .u32 t0, t;\n"
      "mov.u32 t0, %%clock;\n"
      "LAB_SPIN:\n"
      "nanosleep.u32 50;\n"
      "mov.u32 t, %%clock;\nsub.u32 t, t, t0;\nsetp.lt.u32 p, t, %0;\n"
      "@p bra.uni LAB_SPIN;\n}\n" ::"r"(n) : "memory");
}
__device__ __forceinline__ void spin_until(uint32_t t0, uint32_t n) {
  asm volatile("{\n.reg .pred p;\n.reg .u32 t;\nLAB_SPIN:\nmov.u32 t, %%clock;\nsub.u32 t, t, %0;\nsetp.lt.u32 p, t, %1;\n"
               "@p bra.uni LAB_SPIN;\n}\n" ::"r"(t0), "r"(n) : "memory");
}
__device__ __forceinline__ uint32_t now() {
  uint32_t t;
  asm volatile("mov.u32 %0, %%clock;" : "=r"(t)::"memory");
  return t;
}
__device__ __forceinline__ uint32_t stage_enter(uint32_t* ctr, int lane, uint32_t inc) {
  uint32_t old;
  asm volatile("{\n.reg .pred p;\nsetp.eq.u32 p, %2, 0;\nld.relaxed.gpu.global.u32 %0, [%1];\n@p red.relaxed.gpu.global.add.u32 [%1], %3;\n}"
               : "=r"(old) : "l"(ctr), "r"(lane), "r"(inc) : "memory");
  return old;
}
__device__ __forceinline__ void stage_wait(const uint32_t* ctr, uint32_t old) {
  asm volatile(
      "{\n.reg .pred p;\n.reg .u32 v, i;\n"
      "mov.u32 i, 0;\n"
      "LAB_POLL:\n"
      "ld.acquire.gpu.global.u32 v, [%0];\n"
      "xor.b32 v, v, %1;\nsetp.lt.s32 p, v, 0;\n"
      "@p bra.uni LAB_OUT;\n"
      "add.u32 i, i, 1;\nsetp.lt.u32 p, i, 4000000;\n"
      "@p bra.uni LAB_POLL;\n"
      "trap;\n"
      "LAB_OUT:\n"
      "fence.proxy.async.global;\n}\n" ::"l"(ctr), "r"(old) : "memory");
}
__device__ __forceinline__ void cluster_arrive_relaxed() { asm volatile("barrier.cluster.arrive.relaxed.aligned;" ::: "memory"); }
__device__ __forceinline__ void cluster_wait() { asm volatile("barrier.cluster.wait.acquire.aligned;" ::: "memory"); }

__host__ __device__ constexpr uint32_t h2const(float v) {
  double a = v < 0 ? -v : v;
  int e = 15;
  while (a >= 2) { a /= 2; e++; }
  while (a < 1) { a *= 2; e--; }
  const uint32_t h = (v < 0 ? 0x8000u : 0u) | ((e << 10) + (uint32_t)((a - 1) * 1024 + 0.5));
  return h | h << 16;
}
__device__ __forceinline__ uint32_t hfma2(uint32_t a, uint32_t b, uint32_t c) {
  uint32_t d;
  asm("fma.rn.f16x2 %0, %1, %2, %3;" : "=r"(d) : "r"(a), "r"(b), "r"(c));
  return d;
}
__device__ __forceinline__ uint32_t bmul2(uint32_t a, uint32_t b) {
  uint32_t d;
  asm("mul.rn.bf16x2 %0, %1, %2;" : "=r"(d) : "r"(a), "r"(b));
  return d;
}
__device__ __forceinline__ uint2 fma4(uint32_t k, const uint2& a, const uint2& c) { return make_uint2(hfma2(k, a.x, c.x), hfma2(k, a.y, c.y)); }
__device__ __forceinline__ uint32_t pack_bf16(float lo, float hi) {
  uint32_t d;
  asm("cvt.rn.bf16x2.f32 %0, %1, %2;" : "=r"(d) : "f"(hi), "f"(lo));
  return d;
}
__device__ __forceinline__ uint32_t pack_f16(float lo, float hi) {
  uint32_t d;
  asm("cvt.rn.f16x2.f32 %0, %1, %2;" : "=r"(d) : "f"(hi), "f"(lo));
  return d;
}

template <int AOFF, int BOFF>
__device__ __forceinline__ void wgmma192(uint32_t (&d)[48], uint64_t da, uint64_t db, uint32_t scale_d) {
  asm volatile(
      "{\n.reg .pred p;\n.reg .b64 qa, qb;\n"
      "setp.ne.b32 p, %50, 0;\n"
      "add.s64 qa, %48, %51;\nadd.s64 qb, %49, %52;\n"
      "wgmma.mma_async.sync.aligned.m64n192k16.f16.f16.f16 "
      "{%0, %1, %2, %3, %4, %5, %6, %7, %8, %9, %10, %11, %12, %13, %14, %15, "
      "%16, %17, %18, %19, %20, %21, %22, %23, %24, %25, %26, %27, %28, %29, %30, %31, "
      "%32, %33, %34, %35, %36, %37, %38, %39, %40, %41, %42, %43, %44, %45, %46, %47}, "
      "qa, qb, p, 1, 1, 0, 0;\n}\n"
      : "+r"(d[0]), "+r"(d[1]), "+r"(d[2]), "+r"(d[3]), "+r"(d[4]), "+r"(d[5]), "+r"(d[6]), "+r"(d[7]), "+r"(d[8]),
        "+r"(d[9]), "+r"(d[10]), "+r"(d[11]), "+r"(d[12]), "+r"(d[13]), "+r"(d[14]), "+r"(d[15]), "+r"(d[16]),
        "+r"(d[17]), "+r"(d[18]), "+r"(d[19]), "+r"(d[20]), "+r"(d[21]), "+r"(d[22]), "+r"(d[23]), "+r"(d[24]),
        "+r"(d[25]), "+r"(d[26]), "+r"(d[27]), "+r"(d[28]), "+r"(d[29]), "+r"(d[30]), "+r"(d[31]), "+r"(d[32]),
        "+r"(d[33]), "+r"(d[34]), "+r"(d[35]), "+r"(d[36]), "+r"(d[37]), "+r"(d[38]), "+r"(d[39]), "+r"(d[40]),
        "+r"(d[41]), "+r"(d[42]), "+r"(d[43]), "+r"(d[44]), "+r"(d[45]), "+r"(d[46]), "+r"(d[47])
      : "l"(da), "l"(db), "r"(scale_d), "n"(AOFF >> 4), "n"(BOFF >> 4));
}
__device__ __forceinline__ void wg_fence() { asm volatile("wgmma.fence.sync.aligned;" ::: "memory"); }
__device__ __forceinline__ void wg_commit() { asm volatile("wgmma.commit_group.sync.aligned;" ::: "memory"); }
template <int N>
__device__ __forceinline__ void wg_wait() { asm volatile("wgmma.wait_group.sync.aligned %0;" ::"n"(N) : "memory"); }
__device__ __forceinline__ void reg_fence(uint32_t (&d)[48]) {
#pragma unroll
  for (int i = 0; i < 48; i++) asm volatile("" : "+r"(d[i])::"memory");
}

constexpr uint32_t X_EXP = 17;
constexpr uint32_t X_LIM = ((15 + 8) << 7) - 1;
constexpr uint32_t U_LIM = ((15 + 6) << 10) - 1;
constexpr float W_MIN = 1.f / 8192;
constexpr uint32_t Y_MIN = 0x3C00, Y_INF = 0x7C00;
constexpr uint32_t NAN2 = 0x7FFF7FFFu;
using Sample = uint4;
__device__ __forceinline__ uint4 ldg128(const uint4* p) {
  uint4 v;
  asm volatile("ld.global.v4.u32 {%0,%1,%2,%3}, [%4];" : "=r"(v.x), "=r"(v.y), "=r"(v.z), "=r"(v.w) : "l"(p));
  return v;
}
__device__ __forceinline__ Sample sample_w(const __nv_bfloat16* w, int lane) {
  const int q = lane >> 3;
  return ldg128((const uint4*)(w + ((q == 0 ? 1 : q == 1 ? 3 : 4) * CH + 47 * q) * CH + 64 * (q % 3)) + (lane & 7));
}
__device__ __forceinline__ Sample sample_x(const __nv_bfloat16* x, int r, int lane) {
  return ldg128((const uint4*)(x + (size_t)(((r >> 3) * 8 + 1 + lane % 6) * IMG + (r & 7) * 64 + 2 * lane) * CH) + lane % 24);
}
__device__ __forceinline__ uint32_t sample_exp(const Sample& s) {
  const uint32_t m = __vmaxu2(__vimax3_u16x2(s.x & NAN2, s.y & NAN2, s.z & NAN2), s.w & NAN2);
  return __reduce_max_sync(0xffffffffu, max(m & 0xFFFFu, m >> 16)) >> 7;
}

constexpr int NP = 16, NTASK = NSUB * 36, NROUND = (NTASK + 8 * NP - 1) / (8 * NP), NSTAGE = 3;
__host__ __device__ constexpr int stage_end(int k) { return k == 0 ? 1 : k == 1 ? 3 : 2 * NROUND; }
__host__ __device__ constexpr int stage_first(int k) {
  for (int i = 0; i < NSTEP; i++)
    if (step_p(head(i)) / 4 * NROUND * 8 * NP + (step_n(head(i)) + 1) * 36 > stage_end(k - 1) * 8 * NP) return i;
  return -1;
}
static_assert(utrigger(stage_first(1)) >= 0 && stage_first(2) > stage_first(1), "stages");
struct Task {
  uint32_t n, s, kh, k;
  __device__ __forceinline__ Task(uint32_t t, int lane) {
    const uint32_t sub = t % 36;
    n = t / 36, s = sub / 12, kh = (sub / 6) & 1, k = sub % 6 * 32 + lane;
  }
};
constexpr int WTASK = 24 * 64;
__device__ __forceinline__ void prep_load(uint32_t dst, const __nv_bfloat16* __restrict__ w, uint32_t t, int lane) {
  const Task q(min(t, NTASK - 1), 0);
  w += ((q.s * 24 + 2 * q.n + q.kh) * 8 + (lane >> 2)) * CH + q.k + (lane & 3) * 8;
#pragma unroll
  for (int r = 0; r < 3; r++)
    asm volatile("cp.async.cg.shared.global [%0], [%1], 16;" ::"r"(dst + r * 512 + lane * 16), "l"(w + r * 3 * CH * CH) : "memory");
}
__device__ __forceinline__ void prep_store(const float (&g)[3][8], bool tiny, uint4* u, uint32_t t, bool h, int lane) {
  const Task q(t, lane);
  const uint32_t n = q.n, s = q.s, kh = q.kh, k = q.k;
  const uint32_t jn = (k >> 5) * 4 + ((k >> 1) & 3), row = ((k >> 3) & 3) * 2 + (k & 1);
  u += (((h ? 4 * NSUB : 0) + n) * USLAB + s * UTILE + jn * 256 + kh * 128 + row * 16) >> 4;
  constexpr float nA = -1.f / (2.f * A2 * DD), nB = 1.f / (2.f * B2 * DD);
  constexpr float f0 = nA / S1, f1 = nA / S2, f2 = nB / S3, f3 = nB / S4, f4 = 1.f / (A2 * B2);
  const float co[4][3] = {{h ? f4 : f0, h ? 0.f : PA * f0, h ? 0.f : A2 * f0},
                          {h ? 0.f : f1, h ? 0.f : -PA * f1, h ? 1.f : A2 * f1},
                          {f2, PB * f2, B2 * f2},
                          {f3, -PB * f3, B2 * f3}};
#pragma unroll
  for (int p = 0; p < 4; p++) {
    if (p == 2 && h) break;
    uint32_t o[4];
#pragma unroll
    for (int e = 0; e < 4; e++) {
      float v[2];
#pragma unroll
      for (int q = 0; q < 2; q++) v[q] = co[p][0] * g[0][2 * e + q] + co[p][1] * g[1][2 * e + q] + co[p][2] * g[2][2 * e + q];
      const uint32_t b = pack_bf16(v[0], v[1]);
      o[e] = pack_f16(__uint_as_float(b << 16), __uint_as_float(b & 0xFFFF0000u));
    }
    constexpr uint32_t lim = U_LIM * 0x10001u;
    if (__vimax3_u16x2(__vimax3_u16x2(lim, o[0] & NAN2, o[1] & NAN2), o[2] & NAN2, o[3] & NAN2) != lim || tiny) o[0] = NAN2;
    u[p * NSUB * USLAB / 16] = make_uint4(o[0], o[1], o[2], o[3]);
  }
}

constexpr int ROWB = IMG * CH * 2;

__device__ __forceinline__ int region_px(int r) { return (r >> 3) * 8 * IMG + (r & 7) * 64; }
__device__ __forceinline__ int halo_x(int r) { return (r & 7) * 64 - 1; }
__device__ __forceinline__ int halo_y(int r) { return (r >> 3) * 8 - 1; }

__device__ __noinline__ void direct_patch(const __nv_bfloat16* __restrict__ x, const __nv_bfloat16* __restrict__ w,
                                          __nv_bfloat16* __restrict__ out, int y0, int x0, int lane) {
  const int g = lane >> 2, t = lane & 3;
#pragma unroll 1
  for (int k0 = 0; k0 < CH; k0 += 48) {
    float acc[4][6][4] = {};
#pragma unroll 1
    for (int rs = 0; rs < 9; rs++) {
      const int iy = y0 + rs / 3 - 1, ix = x0 + rs % 3 - 1 + g;
#pragma unroll 2
      for (int c = 4 * t; c < CH; c += 16) {
        uint32_t b[6][2];
#pragma unroll
        for (int m = 0; m < 6; m++) {
          const uint32_t* p = (const uint32_t*)(w + (rs * CH + c + (m & 1) * 2) * CH + k0 + (m >> 1) * 16 + 2 * g);
          const uint32_t lo = p[0], hi = p[CH / 2];
          b[m & 6][m & 1] = __byte_perm(lo, hi, 0x5410);
          b[m | 1][m & 1] = __byte_perm(lo, hi, 0x7632);
        }
#pragma unroll
        for (int y = 0; y < 4; y++) {
          uint2 a[2];
#pragma unroll
          for (int h = 0; h < 2; h++)
            a[h] = (unsigned)(iy + y) < IMG && (unsigned)(ix + 8 * h) < IMG ? *(const uint2*)(x + ((iy + y) * IMG + ix + 8 * h) * CH + c)
                                                                           : make_uint2(0, 0);
#pragma unroll
          for (int m = 0; m < 6; m++)
            asm("mma.sync.aligned.m16n8k16.row.col.f32.bf16.bf16.f32 {%0,%1,%2,%3}, {%4,%5,%6,%7}, {%8,%9}, {%0,%1,%2,%3};"
                : "+f"(acc[y][m][0]), "+f"(acc[y][m][1]), "+f"(acc[y][m][2]), "+f"(acc[y][m][3])
                : "r"(a[0].x), "r"(a[1].x), "r"(a[0].y), "r"(a[1].y), "r"(b[m][0]), "r"(b[m][1]));
        }
      }
    }
#pragma unroll
    for (int y = 0; y < 4; y++)
#pragma unroll
      for (int m = 0; m < 6; m += 2)
#pragma unroll
        for (int h = 0; h < 2; h++)
          *(uint2*)(out + ((y0 + y) * IMG + x0 + g + 8 * h) * CH + k0 + m * 8 + 4 * t) =
              make_uint2(pack_bf16(acc[y][m][2 * h], acc[y][m + 1][2 * h]), pack_bf16(acc[y][m][2 * h + 1], acc[y][m + 1][2 * h + 1]));
  }
}

struct Descs { uint64_t a[2][6], b[22]; };
__host__ __device__ constexpr int slot_use(int i) {
  int c = 0;
  for (int j = 0; j < i; j++) c += vslot(step_p(j), step_n(j)) == vslot(step_p(i), step_n(i));
  return c;
}

__host__ __device__ constexpr int out_time(int q) {
  constexpr int t[24] = {
      49, 50, 51, 52, 54, 55, 56, 57, 59, 60, 61, 63, 64, 65, 66, 68, 69, 70, 72, 74, 76, 78, 80, 82};
  return t[q];
}
__host__ __device__ constexpr int out_at(int t) {
  for (int q = 0; q < 24; q++)
    if (out_time(q) % NSTEP == t) return q;
  return -1;
}
__host__ __device__ constexpr bool out_ok() {
  for (int q = 0; q < 24; q++)
    if (out_time(q) <= last_on(q / 6) || out_time(q) < PIV + (q < 12 ? 4 : 6) || out_time(q) >= first_on(q / 6) + NSTEP ||
        (q && out_time(q) <= out_time(q - 1)))
      return false;
  return true;
}
static_assert(out_ok(), "output plan");
constexpr int OUT_END = out_time(23) + 1 - NSTEP;

struct Consumer {
  uint32_t c1[48], c2[48], c3[48], c4[48];
  const uint64_t *descA, *descB;
  static constexpr uint32_t sb = SMEM_BASE;
  uint8_t* pout;
  int bid, nblk, nlong;
  uint32_t done;
  uint32_t osc, ymax[2];
  bool lead, ok, odd;

  uint32_t one;
  __device__ __forceinline__ bool always() {
    uint32_t v = one;
    asm volatile("" : "+r"(v));
    return v != 0;
  }
  __device__ __forceinline__ void axpy(uint32_t (&a)[48], uint32_t k, uint32_t (&b)[48]) {
    if (always()) {
      reg_fence(a); reg_fence(b);
#pragma unroll
      for (int i = 0; i < 48; i++) {
        a[i] = hfma2(k, b[i], a[i]);
        if (i % 12 == 11) {
          asm volatile("" : "+r"(a[i])::"memory");
          sched_barrier();
        }
      }
      reg_fence(a);
    }
  }
  uint32_t pa[4], pb[4], px[4];
  __device__ __forceinline__ uint32_t to_bf16(uint32_t h, uint32_t& m) {
    float lo, hi;
    asm("{\n.reg .b16 l, h;\n.reg .b32 m;\nmov.b32 {l, h}, %3;\ncvt.f32.f16 %0, l;\ncvt.f32.f16 %1, h;\n"
        "abs.f16x2 m, %3;\nmax.NaN.f16x2 %2, m, %2;\n}\n" : "=f"(lo), "=f"(hi), "+r"(m) : "r"(h));
    return bmul2(pack_bf16(lo, hi), osc);
  }
  template <int Q, int EXTRA>
  __device__ __forceinline__ void stg(const uint32_t (&v)[4]) {
    constexpr int y = Q < 6 ? 1 : Q < 12 ? 2 : Q < 18 ? 0 : 3;
    asm volatile("st.global.cs.v4.u32 [%0+%5], {%1,%2,%3,%4};" ::"l"(pout), "r"(v[0]), "r"(v[1]), "r"(v[2]), "r"(v[3]),
                 "n"(y * ROWB + (Q / 3) % 2 * 8 * (CH * 2) + Q % 3 * 128 + EXTRA) : "memory");
  }
  template <int Q, bool YIELD>
  __device__ __forceinline__ void convert(uint32_t (&a)[4], uint32_t (&b)[4], uint32_t (&send)[4]) {
    if constexpr (Q >= 0) {
      const uint32_t(&d)[48] = Q < 6 ? c1 : Q < 12 ? c2 : Q < 18 ? c3 : c4;
      constexpr int o = 16 * (Q % 3) + (Q / 3) % 2;
#pragma unroll
      for (int e = 0; e < 4; e++) {
        if (YIELD && e % 2 == 0) sched_barrier();
        a[e] = to_bf16(d[o + 2 * e], ymax[o & 1]);
        b[e] = to_bf16(d[o + 8 + 2 * e], ymax[o & 1]);
        send[e] = odd ? a[e] : b[e];
      }
    }
  }
  template <int QW, int QR, bool STEP>
  __device__ __forceinline__ void output() {
    uint32_t u[4], v[4], a[4], b[4], send[4];
    if constexpr (!STEP) convert<QR, false>(a, b, send);
    sched_barrier();
#pragma unroll
    for (int e = 0; e < 4; e++) {
      u[e] = odd ? px[e] : pa[e];
      v[e] = odd ? pb[e] : px[e];
    }
    if constexpr (STEP) {
      convert<QR, true>(a, b, send);
      asm volatile("{\n.reg .pred p;\nsetp.ne.u32 p, %0, 0;\n@p pmevent 0;\n}" ::"r"((uint32_t)ok) : "memory");
      sched_barrier();
    }
    if constexpr (QW >= 0 && STEP) { stg<QW, 0>(u); stg<QW, CH * 2>(v); }
    if constexpr (QR >= 0) {
#pragma unroll
      for (int e = 0; e < 4; e++) px[e] = __shfl_xor_sync(0xffffffffu, send[e], 4), pa[e] = a[e], pb[e] = b[e];
    }
    if constexpr (QW >= 0 && !STEP) { stg<QW, 0>(u); stg<QW, CH * 2>(v); }
    sched_barrier();
  }
  __device__ __forceinline__ void range_check() {
    sched_barrier();
    uint32_t m = __vmaxu2(__byte_perm(ymax[0], ymax[1], 0x5410), __byte_perm(ymax[0], ymax[1], 0x7632));
    m = __vmaxu2(m, __shfl_xor_sync(0xffffffffu, m, 1));
    m = __vmaxu2(m, __shfl_xor_sync(0xffffffffu, m, 2));
    asm volatile("{\n.reg .pred p;\nsetp.ge.u32 p, %2, %3;\n@p st.shared.u8 [%0], %1;\n}" ::"r"(sb + OFF_REDO + (threadIdx.x & ~31u) + done), "r"(1),
                 "r"(max((m & 0xFFFFu) - Y_MIN, (m >> 16) - Y_MIN)), "n"(Y_INF - Y_MIN) : "memory");
    ymax[0] = ymax[1] = 0;
  }
  template <int T, int Q0, int Q1, int Q = Q0>
  __device__ __forceinline__ void flush() {
    if constexpr (Q <= Q1) {
      constexpr int QW = Q > Q0 && out_time((Q + 23) % 24) >= T - 1 ? Q - 1 : -1, QR = Q < Q1 && out_time(Q % 24) >= T ? Q : -1;
      if constexpr (QW >= 0 || QR >= 0) output<QW, QR, false>();
      flush<T, Q0, Q1, Q + 1>();
    }
  }
  template <int I>
  __device__ __forceinline__ void hook() {
    constexpr float LP = PB * (PB - PA) / (2.f * A2), LM = PB * (PB + PA) / (2.f * A2);
    constexpr int QW = out_at((I + NSTEP - 1) % NSTEP), QR = out_at(I);
    if constexpr (QW >= 0 || QR >= 0) output<QW, QR, true>();
    if constexpr (I == 22) {
      static_assert(OUT_END < NHEAD, "pointer update");
      range_check();
      osc = lds32(sb + OFF_OSC);
      const int r = bid + done * nblk, d = region_px(r) - region_px(r - nblk);
      asm volatile("mad.wide.s32 %0, %1, 384, %0;" : "+l"(pout) : "r"(d));
    }
    if constexpr (I == NHEAD) { if (bid >= nlong && done == 0 && !(bid & 3)) spin_cycles(24500); }
    if constexpr (I == 42) { if (bid >= nlong && done == 0 && (bid & 3)) spin_cycles(28000); }
    if constexpr (I == PIV) axpy(c1, h2const(S3 * (B2 / A2) / S1), c3);
    if constexpr (I == PIV) axpy(c2, h2const(S3 * (B2 / A2) / S2), c3);
    if constexpr (I == PIV + 1) axpy(c4, h2const(-S3 / S4), c3);
    if constexpr (I == PIV + 1) axpy(c1, h2const(S4 * LP / S1), c4);
    if constexpr (I == PIV + 2) axpy(c2, h2const(S4 * LM / S2), c4);
    if constexpr (I == PIV + 2) axpy(c3, h2const(S4 * (-DD / A2)), c4);
    if constexpr (I == PIV + 3) { axpy(c1, h2const(-1.f / (2.f * PA)), c2); axpy(c2, h2const(PA), c1); }
    if constexpr (I == PIV + 4) axpy(c4, h2const(A2), c1);
    if constexpr (I == PIV + 5) axpy(c3, h2const(1.f / A2), c2);
  }

  template <int I, int END, bool FIRST = false>
  __device__ __forceinline__ void steps() {
    if constexpr (I < END) {
      constexpr int J = (I + 1) % NSTEP, S = FIRST ? head(I) : I, T = FIRST ? head(J) : J, G = FIRST ? head_gate_of(I) : gate_of(I);
      uint32_t(&d)[48] = step_acc(S) == 0 ? c1 : step_acc(S) == 1 ? c2 : step_acc(S) == 2 ? c3 : c4;
      constexpr int vo = vslot(step_p(S), step_n(S)) * VSLOT, uo = USLOT<I> * USLAB;
      if (!ok) {
        mbar_wait_short(sb + BAR_UFULL + 8 * USLOT<I>, UUSE<I> & 1);
        if constexpr (first_use(step_n(S)) == S) mbar_wait_short(sb + BAR_VFULL + 8 * (step_n(S) % NB), step_n(S) / NB);
      }
      const uint64_t da = descA[FIRST ? 4 : slot_use(I)], db = descB[(FIRST ? 16 : 0) + UUSE<I>];
      wg_fence();
      wgmma192<vo, uo>(d, da, db, first_on(step_acc(S)) == S ? 0u : 1u);
      wgmma192<vo + 16, uo + UTILE>(d, da, db, 1u);
      wgmma192<vo + 32, uo + 2 * UTILE>(d, da, db, 1u);
      wg_commit();
      ok = mbar_test(sb + BAR_UFULL + 8 * USLOT<J>, UUSE<J> & 1);
      if constexpr (first_use(step_n(T)) == T) ok &= mbar_test(sb + BAR_VFULL + 8 * (step_n(T) % NB), step_n(T) / NB);
      if constexpr (!FIRST) hook<I>();
      wg_wait<0>();
      reg_fence(d);
      if (lead) mbar_arrive(sb + BAR_UEMPTY + 8 * USLOT<I>);
      if constexpr (G >= 0) { if (lead) mbar_arrive(sb + BAR_GATE + 8 * (G % NB)); }
      steps<I + 1, END, FIRST>();
    }
  }
  template <int I>
  __device__ __forceinline__ void chain() {
    if constexpr (I < NSTEP) {
      static_assert(step_acc(I) == 3 && NSTEP - I <= NU, "chain");
      constexpr int vo = vslot(step_p(I), step_n(I)) * VSLOT, uo = USLOT<I> * USLAB;
      mbar_wait_short(sb + BAR_UFULL + 8 * USLOT<I>, UUSE<I> & 1);
      const uint64_t da = descA[5], db = descB[21];
      wg_fence();
      wgmma192<vo, uo>(c4, da, db, 1u);
      wgmma192<vo + 16, uo + UTILE>(c4, da, db, 1u);
      wgmma192<vo + 32, uo + 2 * UTILE>(c4, da, db, 1u);
      wg_commit();
      chain<I + 1>();
    }
  }
  template <int I>
  __device__ __forceinline__ void release() {
    if constexpr (I < NSTEP) {
      if (lead) mbar_arrive(sb + BAR_UEMPTY + 8 * USLOT<I>);
      release<I + 1>();
    }
  }
  template <int T>
  __device__ __forceinline__ void finish(bool second) {
    if (second) {
      flush<T, 0, 18>();
      asm volatile("bar.sync 1, 256;" ::: "memory");
    }
    chain<T>();
    if (!second) {
      asm volatile("bar.arrive 1, 256;" ::: "memory");
      flush<T, 0, 18>();
    }
    wg_wait<0>();
    reg_fence(c4);
    release<T>();
    done++;
    flush<T, 18, 24>();
  }
};

struct SlotTab { uint32_t off[NSUB][8]; };
constexpr SlotTab make_slots() {
  SlotTab t = {};
  for (int n = 0; n < NSUB; n++)
    for (int p = 0; p < 6; p++) t.off[n][p] = vslot(p, n) * VSLOT;
  return t;
}
__constant__ __align__(64) SlotTab c_slots = make_slots();

constexpr int PF_X = 22, PF_BYTES = PF_X * 2 * 16, PF_NB = 12, U_LEAD = 10;
static_assert(PF_BYTES + 64 <= OFF_U - OFF_SINK, "sink");
__host__ __device__ constexpr uint32_t pf_box(int k) { return 1u << 31 | (k / PF_NB / 3) << 30 | (k / PF_NB % 3) << 28 | (k % PF_NB) << 24; }
__host__ __device__ constexpr int slab_of(int i) { return step_p(i % NSTEP) * NSUB + step_n(i % NSTEP); }
struct LoadTab { uint32_t e[2 * NSTEP]; };
constexpr LoadTab make_loads() {
  LoadTab t = {};
  constexpr int win[6] = {25, 42, 45, 72, 73, 96};
  for (int k = 0, i = 0; k < 6 * PF_NB; k++) {
    const int g = k / PF_NB % 3, when = win[2 * g] + k % PF_NB * (win[2 * g + 1] - win[2 * g]) / PF_NB - (k < 3 * PF_NB ? NSTEP : 0);
    if (when >= 0 && when < NSTEP) t.e[NSTEP + when] = pf_box(k);
    if (k < PF_NB) continue;
    if (i < when) i = when;
    if (i < NSTEP) t.e[i++] = pf_box(k);
  }
  for (int i = 0; i < 2 * NSTEP; i++) {
    int d = 1;
    while (uslot((i + d) % NSTEP) != uslot(i % NSTEP)) d++;
    if (d > NU + 1) d = 0;
    t.e[i] |= (uuse(i % NSTEP) & 1) << 23 | uslot(i % NSTEP) << 20 | d << 16 | slab_of(i + U_LEAD) << 8 | slab_of(head(i + d));
  }
  return t;
}
__constant__ __align__(64) LoadTab c_load = make_loads();

template <int I>
__device__ __forceinline__ void first_slabs(const uint8_t* u) {
  if constexpr (utrigger(I) < 0) {
    constexpr int slab = slab_of(head(I));
    load_u_warp(SMEM_BASE + OFF_U + USLOT<I> * USLAB, u + slab * USLAB, SMEM_BASE + BAR_UFULL + 8 * USLOT<I>);
    first_slabs<I + 1>(u);
  }
}

template <int BYTES>
__device__ __forceinline__ uint32_t warm(const void* p, uint32_t zero) {
  uint32_t v = ~0u;
#pragma unroll
  for (int o = 0; o < BYTES; o += 64) v &= ((const uint32_t*)p)[o / 4 + zero];
  return v;
}

__global__ void __launch_bounds__(384, 1) __cluster_dims__(1, 1, 1)
conv_kernel(const __grid_constant__ CUtensorMap tmX, const __grid_constant__ CUtensorMap tmH, const __grid_constant__ CUtensorMap tmP,
            const __nv_bfloat16* __restrict__ xin, const __nv_bfloat16* __restrict__ wgt, __nv_bfloat16* __restrict__ out,
            uint4* ubuf, uint32_t* arrived, int nblk, int nlong, int nmax, const __grid_constant__ Descs desc) {
  extern __shared__ uint8_t smem_raw[];
  const int tid = threadIdx.x, lane = tid & 31, bid = blockIdx.x;
  const int pidx = bid - (nblk - NP);
  constexpr uint32_t sb = SMEM_BASE;
  uint32_t epoch = 0;
  if (tid < 256) {
    cluster_arrive_relaxed();
    if (pidx >= 0) {
      const uint32_t t0 = pidx * 8 + (tid >> 5), wsm = sb + OFF_V + (tid >> 5) * NROUND * WTASK;
      prep_load(wsm, wgt, t0, lane);
      const Sample ws = sample_w(wgt, lane);
      sched_barrier();
      const float sw = __uint_as_float(max(253 - (int)sample_exp(ws), 0) << 23);
      const int klane = (lane & 6) * 4 + (lane >> 3) * 2 + (lane & 1);
      int stage = 0;
#pragma unroll 1
      for (int round = 0; round < 2 * NROUND; round++) {
        const int k = round < NROUND ? round : round - NROUND;
        asm volatile("cp.async.wait_all;" ::: "memory");
        __syncwarp();
        float g[3][8], gmax = 0.f;
#pragma unroll
        for (int i = 0; i < 24; i++) {
          uint16_t v;
          asm volatile("ld.shared.u16 %0, [%1];" : "=h"(v) : "r"(wsm + k * WTASK + i * 64 + klane * 2) : "memory");
          g[i / 8][i % 8] = __uint_as_float((uint32_t)v << 16);
        }
        if (round >= NROUND) {
#pragma unroll
          for (int i = 0; i < 24; i++) gmax = fmaxf(gmax, fabsf(g[i / 8][i % 8]));
          sched_barrier();
        }
#pragma unroll
        for (int i = 0; i < 24; i++) g[i / 8][i % 8] *= sw;
        if (t0 + k * 8 * NP < NTASK) prep_store(g, gmax > 0.f && gmax * sw < W_MIN, ubuf, t0 + k * 8 * NP, round >= NROUND, klane);
        if (round + 1 == stage_end(0) || round + 1 == stage_end(1) || round + 1 == stage_end(2)) {
          if (++stage == NSTAGE) {
            fence_async();
            asm volatile("ld.relaxed.gpu.global.u32 %0, [%1];" : "=r"(epoch) : "l"(arrived + 32 * NSTAGE) : "memory");
          }
          asm volatile("bar.sync 1, 256;" ::: "memory");
          if (tid == 0)
            asm volatile("red.release.gpu.global.add.u32 [%0], %1;" ::"l"(arrived + 32 * stage), "r"(pidx ? 1 : 0x80000001u - NP) : "memory");
          asm volatile("bar.sync 1, 256;" ::: "memory");
          if (stage == 1) {
#pragma unroll 1
            for (int j = 1; j < NROUND; j++) prep_load(wsm + j * WTASK, wgt, t0 + j * 8 * NP, lane);
          }
        }
      }
      if (tid < 32) asm volatile("bar.arrive 2, 64;" ::: "memory");
    } else if (tid < 32) {
      epoch = stage_enter(arrived, lane, 1);
      spin_until(now(), 2200);
    }
  }
  if (tid >= 352) {
    asm volatile("prefetch.tensormap [%0];" ::"l"(&tmX) : "memory");
    constexpr uint64_t twos = ((2ull << NU) - 1) << (BAR_UEMPTY - OFF_BAR) / 8 | ((1ull << 2 * NB) - 1) << (BAR_VFULL - OFF_BAR) / 8;
    constexpr uint64_t threes = ((1ull << NB) - 1) << (BAR_VFULL - OFF_BAR) / 8;
    if (lane == 0) {
#pragma unroll
      for (int i = 0; i < NBAR; i++) mbar_init(sb + OFF_BAR + 8 * i, 1 + ((twos >> i) & 1) + ((threes >> i) & 1));
      asm volatile("fence.mbarrier_init.release.cluster;" ::: "memory");
      fence_async();
    }
    __syncwarp();
    cluster_arrive_relaxed();
    epoch = stage_enter(arrived, lane, pidx ? 1 : 0x80000001u + NP - 2 * nblk);
    if (pidx >= 0) asm volatile("bar.sync 2, 64;" ::: "memory");
    const uint32_t t0 = now();
#pragma unroll 1
    for (int k = 0, box = 0; k < 9; k++, box = box < 6 ? box + 3 : box - 5) {
      if (pidx < 0) spin_until(t0, min(k, 7) * 410);
      tma_box_warp(sb + OFF_X + box * XBOX, k < 8 ? &tmX : &tmH, sb + BAR_XFULL + 8 * box, k < 8 ? XBOX : XHBOX, 0, halo_x(bid) + k * 8,
                   halo_y(bid));
      if (k == 0) asm volatile("prefetch.tensormap [%0];\nprefetch.tensormap [%1];" ::"l"(&tmH), "l"(&tmP) : "memory");
    }
  }
  if (smem_u32(smem_raw) != SMEM_BASE) __trap();
  const int warp = __shfl_sync(0xffffffffu, tid >> 5, 0);

  if (warp < 8) {
    const int wg = warp >> 2;
    if (warp == 7) {
      spin_until(now(), 1300);
      if ((warm<sizeof(SlotTab)>(&c_slots, tid >> 10) & warm<sizeof(LoadTab)>(&c_load, tid >> 10)) == ~0u) __trap();
    }
    cluster_wait();
    if (warp == 0) {
      stage_wait(arrived + 32, __shfl_sync(0xffffffffu, epoch, 0));
      first_slabs<0>((const uint8_t*)ubuf);
    }
    asm volatile("setmaxnreg.inc.sync.aligned.u32 224;");
    Consumer c;
#pragma unroll
    for (int i = 0; i < 48; i++) { c.c1[i] = 0; c.c2[i] = 0; c.c3[i] = 0; c.c4[i] = 0; }
#pragma unroll
    for (int e = 0; e < 4; e++) c.pa[e] = c.pb[e] = c.px[e] = 0;
    c.descA = desc.a[wg];
    c.descB = desc.b;
    c.lead = (tid & 127) == 0;
    c.one = __shfl_sync(0xffffffffu, nblk, 0);
    c.ok = false;
    c.bid = bid;
    c.nblk = nblk;
    c.nlong = nlong;
    c.odd = (lane >> 2) & 1;
    c.pout = (uint8_t*)out + (long long)(region_px(bid - nblk) + wg * 4 * IMG + (warp & 3) * 16 + (lane >> 3) * 2) * (CH * 2) + (lane & 7) * 16;
    c.done = c.osc = c.ymax[0] = c.ymax[1] = 0;
    asm volatile("st.shared.u8 [%0], %1;" ::"r"(sb + OFF_REDO + tid), "r"(0) : "memory");
    constexpr int ROT = 69;
    c.steps<0, NHEAD, true>();
    bool tail = false;
#pragma unroll 1
    do {
      wg_wait<0>();
      if (tail) {
        c.steps<ROT, NSTEP>();
        c.done++;
        c.steps<0, NHEAD>();
      }
      c.steps<NHEAD, ROT>();
      tail = c.always();
    } while (bid + (int)(c.done + 1) * nblk < NREG);
    c.finish<ROT>(wg);
    c.range_check();
    __syncwarp();
    uint32_t redo;
    asm volatile("ld.shared.u8 %0, [%1];" : "=r"(redo) : "r"(sb + OFF_REDO + tid) : "memory");
    redo = __ballot_sync(0xffffffffu, redo) >> 1;
    if (redo) {
      for (int i = 0; i < (int)c.done; i++)
        if ((redo >> i) & 1) {
          const int r = bid + i * nblk;
          direct_patch(xin, wgt, out, (r >> 3) * 8 + wg * 4, (r & 7) * 64 + (warp & 3) * 16, lane);
        }
    }
  } else {
    asm volatile("setmaxnreg.dec.sync.aligned.u32 56;");
    const int nitem = nmax - (bid >= nlong);
    if (warp == 11) {
      const uint8_t* ubase = (const uint8_t*)ubuf;
      epoch = __shfl_sync(0xffffffffu, epoch, 0);
      cluster_wait();
      const uint8_t* uline = ubase + (bid * 2 + lane) * 128;
      const bool ufetch = lane < 2 && bid < USLAB / 256;
      int r = bid, npf = 0, i = 0, tab = 0;
#pragma unroll 1
      for (int left = nitem * NSTEP - 1; left >= 0; left--) {
        const uint32_t e = c_load.e[tab + i], slot = (e >> 20) & 7;
        const uint8_t* src = ubase + (e & 255) * USLAB;
        const uint8_t* pu = uline + ((e >> 8) & 255) * USLAB;
        const uint32_t dst = sb + OFF_U + slot * USLAB, ebar = sb + BAR_UEMPTY + 8 * slot;
        const bool refill = ((e >> 16) & 7) - 1 < (uint32_t)left;
        constexpr int need1 = utrigger(stage_first(1)), need2 = utrigger(stage_first(2)), xslab = slab_of(UX_FIRST);
        if (tab + i == need1 || tab + i == need2) stage_wait(arrived + (i == need1 ? 64 : 96), epoch);
        refill_u(ebar, (e >> 23) & 1, refill, dst, src);
        if (i == UX_GATE) load_u_warp(sb + OFF_V, ubase + xslab * USLAB, sb + BAR_UFULL + 8 * NU);
        const int rr = r + ((e >> 30) & 1) * nblk;
        if ((int)e < 0 && rr < NREG) {
          asm volatile("{\n.reg .pred p;\nelect.sync _|p, 0xffffffff;\n"
                       "@p cp.async.bulk.tensor.3d.shared::cluster.global.mbarrier::complete_tx::bytes [%0], [%1, {%3, %4, %5}], [%2];\n}\n"
                       ::"r"(sb + OFF_SINK), "l"(&tmP), "r"(sb + BAR_SINK), "r"((e >> 22) & 0xC0), "r"(halo_x(rr) + ((e >> 26) & 3) * PF_X),
                       "r"(halo_y(rr) + 1 + ((e >> 23) & 6)) : "memory");
          npf++;
        }
        if (ufetch && tab + i >= NSTEP - U_LEAD && left >= U_LEAD)
          asm volatile("cp.async.ca.shared.global.L2::128B [%0], [%1], 4;" ::"r"(sb + OFF_SINK + PF_BYTES + lane * 4), "l"(pu) : "memory");
        if (++i == NSTEP) { i = 0; r += nblk; tab = NSTEP; }
      }
      if (lane == 0) asm volatile("mbarrier.arrive.expect_tx.shared::cta.b64 _, [%0], %1;" ::"r"(sb + BAR_SINK), "r"(npf * PF_BYTES) : "memory");
      mbar_wait(sb + BAR_SINK, 0);
      asm volatile("cp.async.wait_all;" ::: "memory");
    } else {
      cluster_arrive_relaxed();
      const int w = warp - 8, col = (lane >> 1) & 7, chunk = lane >> 4;
      const uint32_t xbox = sb + OFF_X + w * 3 * XBOX, xbar = sb + BAR_XFULL + 24 * w;
      const uint32_t xl = xbox + col * 32 + ((chunk ^ (col >> 2)) << 4) + (lane & 1) * 8;
      const uint32_t vl = sb + OFF_V + chunk * VROW + w * 128 + (lane & 15) * 8;
      const bool in_row = w < 2 || col < 2;
      const uint32_t pitch2 = w < 2 ? 256 : 64, bytes2 = 10 * pitch2;
      const uint32_t xl2 = w < 2 ? xl + 2 * XBOX : xbox + 2 * XBOX + col * 32 + chunk * 16 + (lane & 1) * 8;
      const CUtensorMap* tm2 = w < 2 ? &tmX : &tmH;
      auto xrow = [&](int j, int i) {
        uint2 v = make_uint2(0, 0);
        if (j < 2 || in_row) v = lds64(j < 2 ? xl + j * XBOX + i * 256 : xl2 + i * pitch2);
        return v;
      };
      const Sample ws = sample_w(wgt, lane), xs = sample_x(xin, bid, lane);
      uint32_t xsc;
      {
        const int ex = sample_exp(xs), eo = ex + (int)sample_exp(ws) - (111 + X_EXP), es = 127 + X_EXP - ex;
        xsc = es >= 1 && eo >= 1 && eo <= 254 ? es * 0x00800080u : NAN2;
        asm volatile("st.shared.u32 [%0], %1;" ::"r"(sb + OFF_OSC), "r"(eo * 0x00800080u) : "memory");
      }
      constexpr uint32_t gate_par = [] {
        uint32_t m = 0;
        for (int n = 0; n < NSUB; n++) m |= (uint32_t)((n / NB) ^ (gate(n % NB) < 0)) << n;
        return m;
      }();
      constexpr uint32_t LIM2 = X_LIM * 0x10001u;
      cluster_wait();
      auto conv = [&](uint2& v, uint32_t m) {
        const uint32_t tx = bmul2(v.x, xsc), ty = bmul2(v.y, xsc), ux = tx & NAN2, uy = ty & NAN2;
        v = make_uint2(ux * 7 + tx, uy * 7 + ty);
        return __vimax3_u16x2(m, ux, uy);
      };
      uint32_t so[6] = {};
      auto planes = [&](const uint2* h, uint32_t m, uint32_t a, bool on) {
        constexpr uint32_t NB2 = h2const(-B2), NA2 = h2const(-A2);
        const uint2 e1 = fma4(NB2, h[2], h[4]), e2 = fma4(NA2, h[2], h[4]);
        store_v(a + so[4], fma4(NA2, fma4(NB2, h[0], h[2]), e1), on);
        const uint2 o1 = fma4(NB2, h[1], h[3]), o2 = fma4(NA2, h[1], h[3]);
        store_v(a + so[5], fma4(NA2, o1, fma4(NB2, h[3], h[5])), on);
        uint2 v = fma4(h2const(PA), o1, e1);
        if (m != LIM2) v.x = NAN2;
        store_v(a + so[0], v, on);
        store_v(a + so[1], fma4(h2const(-PA), o1, e1), on);
        store_v(a + so[2], fma4(h2const(PB), o2, e2), on);
        store_v(a + so[3], fma4(h2const(-PB), o2, e2), on);
      };
      int r = bid, n = 0;
      uint32_t par = 0;
#pragma unroll 1
      for (int left = nitem * NSUB; left > 0; left--) {
        const int nb = n >= NB ? n - NB : n;
        uint2 d[10];
        mbar_wait(xbar, par);
#pragma unroll
        for (int i = 0; i < 6; i++) d[i] = xrow(0, i);
#pragma unroll
        for (int p = 0; p < 6; p++) so[p] = c_slots.off[n][p];
        const uint32_t gpar = (gate_par >> n) & 1;
        if (++n == NSUB) { n = 0; r += nblk; }
        const int fc = n * 16, fx = halo_x(r) + w * 8, fy = halo_y(r);
#pragma unroll
        for (int j = 0; j < 3; j++) {
          const bool on = j < 2 || in_row;
#pragma unroll
          for (int i = 6; i < 10; i++) d[i] = xrow(j, i);
          const bool xok = j < 2 && mbar_test(xbar + 8 * (j + 1), par);
          sched_barrier();
          const uint32_t m45 = conv(d[5], conv(d[4], LIM2));
          const uint32_t ma = conv(d[3], conv(d[1], conv(d[0], conv(d[2], m45))));
          if (j == 0) mbar_wait(sb + BAR_GATE + 8 * nb, gpar);
          planes(d, ma, vl + j * 384, on);
          sched_barrier();
          const uint32_t mb = conv(d[9], conv(d[7], conv(d[6], conv(d[8], m45))));
          if (left > 1)
            tma_box_warp(xbox + j * XBOX, j < 2 ? &tmX : tm2, xbar + 8 * j, (j < 2 ? XBOX : bytes2) | (mb & 0x8000u), fc, fx + j * 24, fy);
          uint2 h[6];
#pragma unroll
          for (int i = 0; i < 6; i++) h[i] = d[4 + i];
          if (j < 2) {
            mbar_wait(xbar + 8 * (j + 1), par, xok);
#pragma unroll
            for (int i = 0; i < 6; i++) d[i] = xrow(j + 1, i);
          }
          sched_barrier();
          planes(h, mb, vl + j * 384 + VPIECE, on);
          sched_barrier();
        }
        fence_async();
        asm volatile("{\n.reg .pred p;\nelect.sync _|p, 0xffffffff;\n@p mbarrier.arrive.shared::cta.b64 _, [%0];\n}\n"
                     ::"r"(sb + BAR_VFULL + 8 * nb) : "memory");
        par ^= 1;
      }
    }
  }
}

constexpr uint64_t make_desc(uint32_t off, uint32_t lbo, uint32_t sbo) {
  return (uint64_t)((SMEM_BASE + off) >> 4) | ((uint64_t)(lbo >> 4) << 16) | ((uint64_t)(sbo >> 4) << 32);
}

typedef CUresult (*EncodeFn)(CUtensorMap*, CUtensorMapDataType, cuuint32_t, void*, const cuuint64_t*, const cuuint64_t*,
                             const cuuint32_t*, const cuuint32_t*, CUtensorMapInterleave, CUtensorMapSwizzle,
                             CUtensorMapL2promotion, CUtensorMapFloatOOBfill);

}

extern "C" void kernel_launch(void* const* d_in, const int* in_sizes, int n_in, void* d_out, int out_size) {
  static EncodeFn enc = nullptr;
  static int nblk = 0;
  static uint4* ubuf;
  static uint32_t* arrived;
  if (!enc) {
    cudaGetSymbolAddress((void**)&ubuf, g_U);
    cudaGetSymbolAddress((void**)&arrived, g_arrived);
    cudaDriverEntryPointQueryResult qr;
    cudaGetDriverEntryPoint("cuTensorMapEncodeTiled", (void**)&enc, cudaEnableDefault, &qr);
    cudaFuncSetAttribute(conv_kernel, cudaFuncAttributeMaxDynamicSharedMemorySize, SMEM_BYTES);
    int dev;
    cudaGetDevice(&dev);
    cudaDeviceGetAttribute(&nblk, cudaDevAttrMultiProcessorCount, dev);
  }
  CUtensorMap tmX, tmH, tmP;
  const cuuint64_t dims[3] = {CH, IMG, IMG};
  const cuuint64_t strides[2] = {CH * 2, (cuuint64_t)CH * 2 * IMG};
  const cuuint32_t es[3] = {1, 1, 1};
  const cuuint32_t boxX[3] = {16, 8, 10}, boxH[3] = {16, 2, 10}, boxP[3] = {8, PF_X, 2};
  enc(&tmH, CU_TENSOR_MAP_DATA_TYPE_BFLOAT16, 3, d_in[0], dims, strides, boxH, es, CU_TENSOR_MAP_INTERLEAVE_NONE,
      CU_TENSOR_MAP_SWIZZLE_NONE, CU_TENSOR_MAP_L2_PROMOTION_L2_64B, CU_TENSOR_MAP_FLOAT_OOB_FILL_NONE);
  enc(&tmP, CU_TENSOR_MAP_DATA_TYPE_BFLOAT16, 3, d_in[0], dims, strides, boxP, es, CU_TENSOR_MAP_INTERLEAVE_NONE,
      CU_TENSOR_MAP_SWIZZLE_NONE, CU_TENSOR_MAP_L2_PROMOTION_L2_128B, CU_TENSOR_MAP_FLOAT_OOB_FILL_NONE);
  enc(&tmX, CU_TENSOR_MAP_DATA_TYPE_BFLOAT16, 3, d_in[0], dims, strides, boxX, es, CU_TENSOR_MAP_INTERLEAVE_NONE,
      CU_TENSOR_MAP_SWIZZLE_32B, CU_TENSOR_MAP_L2_PROMOTION_L2_64B, CU_TENSOR_MAP_FLOAT_OOB_FILL_NONE);
  Descs desc = {};
  for (int i = 0; i < 6; i++) { desc.a[0][i] = make_desc(OFF_V, VROW, 128); desc.a[1][i] = make_desc(OFF_V + VPIECE, VROW, 128); }
  for (int i = 0; i < 22; i++) desc.b[i] = make_desc(OFF_U, 128, 256);
  conv_kernel<<<nblk, 384, SMEM_BYTES>>>(tmX, tmH, tmP, (const __nv_bfloat16*)d_in[0], (const __nv_bfloat16*)d_in[1],
                                         (__nv_bfloat16*)d_out, ubuf, arrived, nblk, NREG % nblk ? NREG % nblk : nblk, (NREG + nblk - 1) / nblk, desc);
}
```

```cpp
#include <cuda_runtime.h>
#include <cuda_bf16.h>
#include <cuda.h>
#include <stdint.h>

namespace {

constexpr int IMG = 512, CH = 192;
constexpr float PA = 1.5f, PB = 0.6875f;
constexpr float A2 = PA * PA, B2 = PB * PB, DD = B2 - A2;

constexpr int NSTEP = 72, NSUB = 12;
__host__ __device__ constexpr int sched(int i) {
  constexpr int t[NSTEP] = {
      0x00, 0x10, 0x20, 0x01, 0x11, 0x21, 0x02, 0x12, 0x22, 0x03, 0x13, 0x23, 0x30, 0x31, 0x32, 0x33, 0x24, 0x34,
      0x04, 0x14, 0x25, 0x35, 0x05, 0x15, 0x26, 0x36, 0x06, 0x16, 0x27, 0x37, 0x07, 0x17, 0x28, 0x38, 0x08, 0x18,
      0x29, 0x39, 0x09, 0x19, 0x2a, 0x3a, 0x0a, 0x1a, 0x2b, 0x3b, 0x1b, 0x0b, 0x40, 0x4b, 0x50, 0x41, 0x51, 0x4a,
      0x49, 0x48, 0x47, 0x42, 0x52, 0x46, 0x45, 0x5b, 0x44, 0x43, 0x5a, 0x53, 0x59, 0x58, 0x57, 0x56, 0x54, 0x55};
  return t[i];
}
__host__ __device__ constexpr int step_p(int i) { return sched(i) >> 4; }
__host__ __device__ constexpr int step_n(int i) { return sched(i) & 15; }
__host__ __device__ constexpr int step_acc(int i) { return step_p(i) < 4 ? step_p(i) : step_p(i) - 2; }
__host__ __device__ constexpr int first_on(int acc) {
  for (int i = 0; i < NSTEP; i++)
    if (step_acc(i) == acc) return i;
  return -1;
}
__host__ __device__ constexpr int last_on(int acc) {
  for (int i = NSTEP - 1; i >= 0; i--)
    if (step_acc(i) == acc) return i;
  return -1;
}
__host__ __device__ constexpr int find_step(int p, int n) {
  for (int i = 0; i < NSTEP; i++)
    if (sched(i) == p * 16 + n) return i;
  return -1;
}
__host__ __device__ constexpr int first_use(int n) {
  for (int i = 0; i < NSTEP; i++)
    if (step_n(i) == n) return i;
  return -1;
}
constexpr int NHEAD = first_on(3) / 3 * 4;
__host__ __device__ constexpr int head(int i) { return i < NHEAD ? find_step(i % 4, i / 4) : i; }
constexpr float S1 = 1.f / PA, S2 = 1.f / (2.f * A2), S3 = -A2 / (2.f * DD), S4 = -1.f / (PB * DD);
constexpr int PIV = find_step(3, NSUB - 1);
static_assert(find_step(2, NSUB - 1) == PIV - 1 && last_on(1) == PIV + 1 && last_on(0) == PIV + 2 && PIV + 3 == 4 * NSUB &&
              step_p(PIV + 3) == 4 && step_p(PIV + 4) == 4 && step_p(PIV + 5) == 5, "basis change");

constexpr int NV = 32, NB = 6;
__host__ __device__ constexpr int vslot(int p, int n) {
  constexpr int t[6][NSUB] = {
      {31, 19, 25, 18, 19, 27, 21, 4, 24, 26, 3, 26}, {28, 23, 24, 22, 17, 24, 28, 3, 25, 27, 0, 28},
      {27, 17, 14, 20, 23, 22, 20, 31, 0, 28, 1, 2}, {26, 21, 15, 16, 31, 18, 23, 26, 23, 31, 4, 31},
      {7, 6, 8, 10, 12, 14, 15, 17, 19, 21, 23, 27}, {30, 29, 9, 11, 13, 5, 16, 18, 20, 22, 24, 25}};
  return t[p][n];
}
__host__ __device__ constexpr int gate(int n) {
  constexpr int t[NSUB] = {-20, -14, -8, -2, 5, 11, 16, 21, 25, 29, 34, 39};
  return t[n];
}
__host__ __device__ constexpr int gate_of(int i) {
  for (int n = 0; n < NSUB; n++)
    if ((gate(n) + NSTEP) % NSTEP == i) return n;
  return -1;
}
__host__ __device__ constexpr int head_gate_of(int i) {
  for (int n = 0; n < NSUB; n++) {
    int m = -1;
    for (int j = 0; j < NHEAD; j++)
      if (head(j) <= gate(n)) m = j;
    if (gate(n) < NHEAD && m == i) return n;
  }
  return -1;
}
__host__ __device__ constexpr bool gates_ok() {
  int early = 0;
  for (int i = 0; i < NHEAD; i++) early += (gate_of(i) >= 0) - (head_gate_of(i) >= 0) + (head(i) >= NHEAD);
  if (early) return false;
  for (int n = 0; n < NSUB; n++) {
    for (int p = 0; p < 6; p++)
      for (int d = 1; d <= NSUB; d++)
        for (int q = 0; q < 6; q++) {
          const int m = (n - d + NSUB) % NSUB;
          if (vslot(q, m) == vslot(p, n) && (find_step(q, m) - (n - d < 0 ? NSTEP : 0) > gate(n) || (m == n && p != q))) return false;
        }
    if (n > 0 && (gate(n) <= gate(n - 1) || first_use(n) <= first_use(n - 1))) return false;
    if (gate(n) >= first_use(n)) return false;
    if (gate((n + NB) % NSUB) + (n >= NB ? NSTEP : 0) < first_use(n)) return false;
  }
  return gate(0) + NSTEP > gate(NSUB - 1) && gate(NB) >= 0;
}
static_assert(gates_ok(), "gates");

constexpr int UTILE = CH * 16 * 2;
constexpr int USLAB = 3 * UTILE;
constexpr int NU = 4;
constexpr int VROW = 66 * 16;
constexpr int VPIECE = 2 * VROW;
constexpr int VSLOT = 2 * VPIECE;
constexpr int XBOX = 10 * 8 * 32;
constexpr int XHBOX = 10 * 2 * 32;
constexpr int UX_FIRST = 52, UX_COUNT = 8, UX_GATE = UX_FIRST - NU - 1;
__host__ __device__ constexpr bool uextra(int i) {
  const int d = (i - UX_FIRST + NSTEP) % NSTEP;
  return d % (NU + 1) == 0 && d / (NU + 1) < UX_COUNT;
}
__host__ __device__ constexpr int uindex(int i) {
  int c = 0;
  for (int j = 0; j < i; j++) c += uextra(j) == uextra(i);
  return c;
}
__host__ __device__ constexpr int uslot(int i) { return uextra(i) ? NU : uindex(i) % NU; }
__host__ __device__ constexpr int uuse(int i) { return uextra(i) ? uindex(i) : uindex(i) / NU; }
__host__ __device__ constexpr int utrigger(int j) {
  if (j == UX_FIRST) return UX_GATE;
  int i = j - 1;
  while (uslot((i + NSTEP) % NSTEP) != uslot(j)) i--;
  return i;
}
template <int I> constexpr int USLOT = uslot(I);
template <int I> constexpr int UUSE = uuse(I);
__host__ __device__ constexpr bool uring_ok() {
  for (int n = 0; n < NSUB; n++)
    for (int p = 0; p < 6; p++)
      if (vslot(p, n) * VSLOT < USLAB && (find_step(p, n) > UX_GATE || gate(n) < UX_FIRST + (NU + 1) * (UX_COUNT - 1) - NSTEP))
        return false;
  return UX_COUNT % 2 == 0 && (NSTEP - UX_COUNT) % (2 * NU) == 0;
}
static_assert(uring_ok(), "U ring");

constexpr int OFF_X = 0;
constexpr int OFF_SINK = OFF_X + 8 * XBOX + XHBOX;
constexpr int OFF_U = OFF_SINK + 768;
constexpr int OFF_V = OFF_U + NU * USLAB;
constexpr int OFF_BAR = OFF_V + NV * VSLOT;
constexpr int BAR_UFULL = OFF_BAR;
constexpr int BAR_UEMPTY = BAR_UFULL + 8 * (NU + 1);
constexpr int BAR_XFULL = BAR_UEMPTY + 8 * (NU + 1);
constexpr int BAR_VFULL = BAR_XFULL + 8 * 9;
constexpr int BAR_GATE = BAR_VFULL + 8 * NB;
constexpr int BAR_SINK = BAR_GATE + 8 * NB;
constexpr int OFF_OSC = BAR_SINK + 8;
constexpr int NBAR = (OFF_OSC - OFF_BAR) / 8;
constexpr int OFF_REDO = OFF_OSC + 8;
constexpr int SMEM_BYTES = OFF_REDO + 256;
constexpr uint32_t SMEM_BASE = 1024;
static_assert(SMEM_BYTES <= 232448, "smem");

constexpr int NREG = 512;

struct Scratch {
  uint4 u[NSTEP * USLAB / 16];
  uint32_t arrived[4 * 32];
};
__device__ __align__(128) Scratch g_scratch;

__device__ __forceinline__ uint32_t smem_u32(const void* p) { return (uint32_t)__cvta_generic_to_shared(p); }
__device__ __forceinline__ void mbar_init(uint32_t a, int c) {
  asm volatile("mbarrier.init.shared::cta.b64 [%0], %1;" ::"r"(a), "r"(c) : "memory");
}
__device__ __forceinline__ void mbar_arrive(uint32_t a) {
  asm volatile("mbarrier.arrive.shared::cta.b64 _, [%0];" ::"r"(a) : "memory");
}
__device__ __forceinline__ void mbar_wait(uint32_t a, uint32_t parity, uint32_t skip = 0) {
  asm volatile(
      "{\n"
      ".reg .pred p;\n"
      ".reg .u32 n;\n"
      "setp.ne.u32 p, %2, 0;\n"
      "@p bra.uni LAB_DONE;\n"
      "mov.u32 n, 0;\n"
      "LAB_WAIT:\n"
      "mbarrier.try_wait.parity.shared::cta.b64 p, [%0], %1;\n"
      "@p bra.uni LAB_DONE;\n"
      "add.u32 n, n, 1;\n"
      "setp.lt.u32 p, n, 4000000;\n"
      "@p bra.uni LAB_WAIT;\n"
      "trap;\n"
      "LAB_DONE:\n"
      "}\n" ::"r"(a), "r"(parity), "r"(skip) : "memory");
}
__device__ __forceinline__ void mbar_wait_short(uint32_t a, uint32_t parity) {
  asm volatile("{\n.reg .pred p;\nLAB_WAIT:\nmbarrier.try_wait.parity.shared::cta.b64 p, [%0], %1;\n@!p bra.uni LAB_WAIT;\n}\n" ::"r"(a),
               "r"(parity) : "memory");
}
__device__ __forceinline__ bool mbar_test(uint32_t a, uint32_t parity) {
  uint32_t ok;
  asm volatile("{\n.reg .pred p;\nmbarrier.test_wait.parity.shared::cta.b64 p, [%1], %2;\nselp.u32 %0, 1, 0, p;\n}\n"
               : "=r"(ok) : "r"(a), "r"(parity) : "memory");
  return ok;
}
__device__ __forceinline__ void fence_async() { asm volatile("fence.proxy.async.shared::cta;" ::: "memory"); }
__device__ __forceinline__ void tma_box_warp(uint32_t dst, const CUtensorMap* tm, uint32_t bar, uint32_t bytes, int c, int x, int y) {
  asm volatile(
      "{\n.reg .pred p;\nelect.sync _|p, 0xffffffff;\n"
      "@p mbarrier.arrive.expect_tx.shared::cta.b64 _, [%2], %6;\n"
      "@p cp.async.bulk.tensor.3d.shared::cluster.global.mbarrier::complete_tx::bytes [%0], [%1, {%3, %4, %5}], [%2];\n}\n" ::"r"(dst),
      "l"(tm), "r"(bar), "r"(c), "r"(x), "r"(y), "r"(bytes) : "memory");
}
__device__ __forceinline__ void load_u_warp(uint32_t dst, const void* src, uint32_t bar) {
  asm volatile("{\n.reg .pred p;\nelect.sync _|p, 0xffffffff;\n"
               "@p mbarrier.arrive.expect_tx.shared::cta.b64 _, [%2], %3;\n"
               "@p cp.async.bulk.shared::cluster.global.mbarrier::complete_tx::bytes [%0], [%1], %3, [%2];\n}\n" ::"r"(dst),
               "l"(src), "r"(bar), "n"(USLAB) : "memory");
}
__device__ __forceinline__ void refill_u(uint32_t ebar, uint32_t parity, uint32_t on, uint32_t dst, const void* src) {
  asm volatile(
      "{\n.reg .pred p;\n.reg .u32 n;\n"
      "mov.u32 n, 0;\n"
      "LAB_WAIT:\n"
      "mbarrier.try_wait.parity.shared::cta.b64 p, [%0], %1;\n"
      "@p bra.uni LAB_DONE;\n"
      "add.u32 n, n, 1;\nsetp.lt.u32 p, n, 4000000;\n"
      "@p bra.uni LAB_WAIT;\n"
      "trap;\n"
      "LAB_DONE:\n"
      "setp.eq.u32 p, %2, 0;\n"
      "@p bra.uni LAB_OUT;\n"
      "elect.sync _|p, 0xffffffff;\n"
      "@p mbarrier.arrive.expect_tx.shared::cta.b64 _, [%5], %6;\n"
      "@p cp.async.bulk.shared::cluster.global.mbarrier::complete_tx::bytes [%3], [%4], %6, [%5];\n"
      "LAB_OUT:\n}\n" ::"r"(ebar), "r"(parity), "r"(on), "r"(dst), "l"(src), "r"(ebar - (BAR_UEMPTY - BAR_UFULL)), "n"(USLAB) : "memory");
}
__device__ __forceinline__ uint2 lds64(uint32_t a) {
  uint2 v;
  asm volatile("ld.shared.v2.u32 {%0,%1}, [%2];" : "=r"(v.x), "=r"(v.y) : "r"(a) : "memory");
  return v;
}
__device__ __forceinline__ uint32_t lds32(uint32_t a) {
  uint32_t v;
  asm volatile("ld.shared.u32 %0, [%1];" : "=r"(v) : "r"(a) : "memory");
  return v;
}
__device__ __forceinline__ void store_v(uint32_t a, uint2 v, bool on) {
  v.x &= 0xFFFCFFFCu; v.y &= 0xFFFCFFFCu;
  if (on) asm volatile("st.shared.v2.u32 [%0], {%1,%2};" ::"r"(a), "r"(v.x), "r"(v.y) : "memory");
}
__device__ __forceinline__ void sched_barrier() { asm volatile("pmevent 0;" ::: "memory"); }
__device__ __forceinline__ void spin_cycles(uint32_t n) {
  asm volatile(
      "{\n.reg .pred p;\n.reg .u32 t0, t;\n"
      "mov.u32 t0, %%clock;\n"
      "LAB_SPIN:\n"
      "nanosleep.u32 50;\n"
      "mov.u32 t, %%clock;\nsub.u32 t, t, t0;\nsetp.lt.u32 p, t, %0;\n"
      "@p bra.uni LAB_SPIN;\n}\n" ::"r"(n) : "memory");
}
__device__ __forceinline__ void spin_until(uint32_t t0, uint32_t n) {
  asm volatile("{\n.reg .pred p;\n.reg .u32 t;\nLAB_SPIN:\nmov.u32 t, %%clock;\nsub.u32 t, t, %0;\nsetp.lt.u32 p, t, %1;\n"
               "@p bra.uni LAB_SPIN;\n}\n" ::"r"(t0), "r"(n) : "memory");
}
__device__ __forceinline__ uint32_t now() {
  uint32_t t;
  asm volatile("mov.u32 %0, %%clock;" : "=r"(t)::"memory");
  return t;
}
__device__ __forceinline__ uint32_t stage_enter(uint32_t* ctr, int lane, uint32_t inc) {
  uint32_t old;
  asm volatile("{\n.reg .pred p;\nsetp.eq.u32 p, %2, 0;\nld.relaxed.gpu.global.u32 %0, [%1];\n@p red.relaxed.gpu.global.add.u32 [%1], %3;\n}"
               : "=r"(old) : "l"(ctr), "r"(lane), "r"(inc) : "memory");
  return old;
}
__device__ __forceinline__ void stage_wait(const uint32_t* ctr, uint32_t old) {
  asm volatile(
      "{\n.reg .pred p;\n.reg .u32 v, i;\n"
      "mov.u32 i, 0;\n"
      "LAB_POLL:\n"
      "ld.acquire.gpu.global.u32 v, [%0];\n"
      "xor.b32 v, v, %1;\nsetp.lt.s32 p, v, 0;\n"
      "@p bra.uni LAB_OUT;\n"
      "add.u32 i, i, 1;\nsetp.lt.u32 p, i, 4000000;\n"
      "@p bra.uni LAB_POLL;\n"
      "trap;\n"
      "LAB_OUT:\n"
      "fence.proxy.async.global;\n}\n" ::"l"(ctr), "r"(old) : "memory");
}
__device__ __forceinline__ void cluster_arrive_relaxed() { asm volatile("barrier.cluster.arrive.relaxed.aligned;" ::: "memory"); }
__device__ __forceinline__ void cluster_wait() { asm volatile("barrier.cluster.wait.acquire.aligned;" ::: "memory"); }

__host__ __device__ constexpr uint32_t h2const(float v) {
  double a = v < 0 ? -v : v;
  int e = 15;
  while (a >= 2) { a /= 2; e++; }
  while (a < 1) { a *= 2; e--; }
  const uint32_t h = (v < 0 ? 0x8000u : 0u) | ((e << 10) + (uint32_t)((a - 1) * 1024 + 0.5));
  return h | h << 16;
}
__device__ __forceinline__ uint32_t hfma2(uint32_t a, uint32_t b, uint32_t c) {
  uint32_t d;
  asm("fma.rn.f16x2 %0, %1, %2, %3;" : "=r"(d) : "r"(a), "r"(b), "r"(c));
  return d;
}
__device__ __forceinline__ uint32_t bmul2(uint32_t a, uint32_t b) {
  uint32_t d;
  asm("mul.rn.bf16x2 %0, %1, %2;" : "=r"(d) : "r"(a), "r"(b));
  return d;
}
__device__ __forceinline__ uint2 fma4(uint32_t k, const uint2& a, const uint2& c) { return make_uint2(hfma2(k, a.x, c.x), hfma2(k, a.y, c.y)); }
__device__ __forceinline__ uint32_t pack_bf16(float lo, float hi) {
  uint32_t d;
  asm("cvt.rn.bf16x2.f32 %0, %1, %2;" : "=r"(d) : "f"(hi), "f"(lo));
  return d;
}
__device__ __forceinline__ uint32_t pack_f16(float lo, float hi) {
  uint32_t d;
  asm("cvt.rn.f16x2.f32 %0, %1, %2;" : "=r"(d) : "f"(hi), "f"(lo));
  return d;
}

template <int AOFF, int BOFF>
__device__ __forceinline__ void wgmma192(uint32_t (&d)[48], uint64_t da, uint64_t db, uint32_t scale_d) {
  asm volatile(
      "{\n.reg .pred p;\n.reg .b64 qa, qb;\n"
      "setp.ne.b32 p, %50, 0;\n"
      "add.s64 qa, %48, %51;\nadd.s64 qb, %49, %52;\n"
      "wgmma.mma_async.sync.aligned.m64n192k16.f16.f16.f16 "
      "{%0, %1, %2, %3, %4, %5, %6, %7, %8, %9, %10, %11, %12, %13, %14, %15, "
      "%16, %17, %18, %19, %20, %21, %22, %23, %24, %25, %26, %27, %28, %29, %30, %31, "
      "%32, %33, %34, %35, %36, %37, %38, %39, %40, %41, %42, %43, %44, %45, %46, %47}, "
      "qa, qb, p, 1, 1, 0, 0;\n}\n"
      : "+r"(d[0]), "+r"(d[1]), "+r"(d[2]), "+r"(d[3]), "+r"(d[4]), "+r"(d[5]), "+r"(d[6]), "+r"(d[7]), "+r"(d[8]),
        "+r"(d[9]), "+r"(d[10]), "+r"(d[11]), "+r"(d[12]), "+r"(d[13]), "+r"(d[14]), "+r"(d[15]), "+r"(d[16]),
        "+r"(d[17]), "+r"(d[18]), "+r"(d[19]), "+r"(d[20]), "+r"(d[21]), "+r"(d[22]), "+r"(d[23]), "+r"(d[24]),
        "+r"(d[25]), "+r"(d[26]), "+r"(d[27]), "+r"(d[28]), "+r"(d[29]), "+r"(d[30]), "+r"(d[31]), "+r"(d[32]),
        "+r"(d[33]), "+r"(d[34]), "+r"(d[35]), "+r"(d[36]), "+r"(d[37]), "+r"(d[38]), "+r"(d[39]), "+r"(d[40]),
        "+r"(d[41]), "+r"(d[42]), "+r"(d[43]), "+r"(d[44]), "+r"(d[45]), "+r"(d[46]), "+r"(d[47])
      : "l"(da), "l"(db), "r"(scale_d), "n"(AOFF >> 4), "n"(BOFF >> 4));
}
__device__ __forceinline__ void wg_fence() { asm volatile("wgmma.fence.sync.aligned;" ::: "memory"); }
__device__ __forceinline__ void wg_commit() { asm volatile("wgmma.commit_group.sync.aligned;" ::: "memory"); }
template <int N>
__device__ __forceinline__ void wg_wait() { asm volatile("wgmma.wait_group.sync.aligned %0;" ::"n"(N) : "memory"); }
__device__ __forceinline__ void reg_fence(uint32_t (&d)[48]) {
#pragma unroll
  for (int i = 0; i < 48; i++) asm volatile("" : "+r"(d[i])::"memory");
}

constexpr uint32_t X_EXP = 17;
constexpr uint32_t X_LIM = ((15 + 8) << 7) - 1;
constexpr uint32_t U_LIM = ((15 + 6) << 10) - 1;
constexpr float W_MIN = 1.f / 8192;
constexpr uint32_t Y_MIN = 0x3C00, Y_INF = 0x7C00;
constexpr uint32_t NAN2 = 0x7FFF7FFFu;
using Sample = uint4;
__device__ __forceinline__ uint4 ldg128(const uint4* p) {
  uint4 v;
  asm volatile("ld.global.v4.u32 {%0,%1,%2,%3}, [%4];" : "=r"(v.x), "=r"(v.y), "=r"(v.z), "=r"(v.w) : "l"(p));
  return v;
}
__device__ __forceinline__ Sample sample_w(const __nv_bfloat16* w, int lane) {
  const int q = lane >> 3;
  return ldg128((const uint4*)(w + ((q == 0 ? 1 : q == 1 ? 3 : 4) * CH + 47 * q) * CH + 64 * (q % 3)) + (lane & 7));
}
__device__ __forceinline__ Sample sample_x(const __nv_bfloat16* x, int r, int lane) {
  return ldg128((const uint4*)(x + (size_t)(((r >> 3) * 8 + 1 + lane % 6) * IMG + (r & 7) * 64 + 2 * lane) * CH) + lane % 24);
}
__device__ __forceinline__ uint32_t sample_exp(const Sample& s) {
  const uint32_t m = __vmaxu2(__vimax3_u16x2(s.x & NAN2, s.y & NAN2, s.z & NAN2), s.w & NAN2);
  return __reduce_max_sync(0xffffffffu, max(m & 0xFFFFu, m >> 16)) >> 7;
}

constexpr int NP = 16, NTASK = NSUB * 36, NROUND = (NTASK + 8 * NP - 1) / (8 * NP), NSTAGE = 3;
__host__ __device__ constexpr int stage_end(int k) { return k == 0 ? 1 : k == 1 ? 3 : 2 * NROUND; }
__host__ __device__ constexpr int stage_first(int k) {
  for (int i = 0; i < NSTEP; i++)
    if (step_p(head(i)) / 4 * NROUND * 8 * NP + (step_n(head(i)) + 1) * 36 > stage_end(k - 1) * 8 * NP) return i;
  return -1;
}
static_assert(utrigger(stage_first(1)) >= 0 && stage_first(2) > stage_first(1), "stages");
struct Task {
  uint32_t n, s, kh, k;
  __device__ __forceinline__ Task(uint32_t t, int lane) {
    const uint32_t sub = t % 36;
    n = t / 36, s = sub / 12, kh = (sub / 6) & 1, k = sub % 6 * 32 + lane;
  }
};
constexpr int WTASK = 24 * 64;
__device__ __forceinline__ void prep_load(uint32_t dst, const __nv_bfloat16* __restrict__ w, uint32_t t, int lane) {
  const Task q(min(t, NTASK - 1), 0);
  w += ((q.s * 24 + 2 * q.n + q.kh) * 8 + (lane >> 2)) * CH + q.k + (lane & 3) * 8;
#pragma unroll
  for (int r = 0; r < 3; r++)
    asm volatile("cp.async.cg.shared.global [%0], [%1], 16;" ::"r"(dst + r * 512 + lane * 16), "l"(w + r * 3 * CH * CH) : "memory");
}
__device__ __forceinline__ void prep_store(const float (&g)[3][8], bool tiny, uint4* u, uint32_t t, bool h, int lane) {
  const Task q(t, lane);
  const uint32_t n = q.n, s = q.s, kh = q.kh, k = q.k;
  const uint32_t jn = (k >> 5) * 4 + ((k >> 1) & 3), row = ((k >> 3) & 3) * 2 + (k & 1);
  u += (((h ? 4 * NSUB : 0) + n) * USLAB + s * UTILE + jn * 256 + kh * 128 + row * 16) >> 4;
  constexpr float nA = -1.f / (2.f * A2 * DD), nB = 1.f / (2.f * B2 * DD);
  constexpr float f0 = nA / S1, f1 = nA / S2, f2 = nB / S3, f3 = nB / S4, f4 = 1.f / (A2 * B2);
  const float co[4][3] = {{h ? f4 : f0, h ? 0.f : PA * f0, h ? 0.f : A2 * f0},
                          {h ? 0.f : f1, h ? 0.f : -PA * f1, h ? 1.f : A2 * f1},
                          {f2, PB * f2, B2 * f2},
                          {f3, -PB * f3, B2 * f3}};
#pragma unroll
  for (int p = 0; p < 4; p++) {
    if (p == 2 && h) break;
    uint32_t o[4];
#pragma unroll
    for (int e = 0; e < 4; e++) {
      float v[2];
#pragma unroll
      for (int q = 0; q < 2; q++) v[q] = co[p][0] * g[0][2 * e + q] + co[p][1] * g[1][2 * e + q] + co[p][2] * g[2][2 * e + q];
      const uint32_t b = pack_bf16(v[0], v[1]);
      o[e] = pack_f16(__uint_as_float(b << 16), __uint_as_float(b & 0xFFFF0000u));
    }
    constexpr uint32_t lim = U_LIM * 0x10001u;
    if (__vimax3_u16x2(__vimax3_u16x2(lim, o[0] & NAN2, o[1] & NAN2), o[2] & NAN2, o[3] & NAN2) != lim || tiny) o[0] = NAN2;
    u[p * NSUB * USLAB / 16] = make_uint4(o[0], o[1], o[2], o[3]);
  }
}

constexpr int ROWB = IMG * CH * 2;

__device__ __forceinline__ int region_px(int r) { return (r >> 3) * 8 * IMG + (r & 7) * 64; }
__device__ __forceinline__ int halo_x(int r) { return (r & 7) * 64 - 1; }
__device__ __forceinline__ int halo_y(int r) { return (r >> 3) * 8 - 1; }

__device__ __noinline__ void direct_patch(const __nv_bfloat16* __restrict__ x, const __nv_bfloat16* __restrict__ w,
                                          __nv_bfloat16* __restrict__ out, int y0, int x0, int lane) {
  const int g = lane >> 2, t = lane & 3;
#pragma unroll 1
  for (int k0 = 0; k0 < CH; k0 += 48) {
    float acc[4][6][4] = {};
#pragma unroll 1
    for (int rs = 0; rs < 9; rs++) {
      const int iy = y0 + rs / 3 - 1, ix = x0 + rs % 3 - 1 + g;
#pragma unroll 2
      for (int c = 4 * t; c < CH; c += 16) {
        uint32_t b[6][2];
#pragma unroll
        for (int m = 0; m < 6; m++) {
          const uint32_t* p = (const uint32_t*)(w + (rs * CH + c + (m & 1) * 2) * CH + k0 + (m >> 1) * 16 + 2 * g);
          const uint32_t lo = p[0], hi = p[CH / 2];
          b[m & 6][m & 1] = __byte_perm(lo, hi, 0x5410);
          b[m | 1][m & 1] = __byte_perm(lo, hi, 0x7632);
        }
#pragma unroll
        for (int y = 0; y < 4; y++) {
          uint2 a[2];
#pragma unroll
          for (int h = 0; h < 2; h++)
            a[h] = (unsigned)(iy + y) < IMG && (unsigned)(ix + 8 * h) < IMG ? *(const uint2*)(x + ((iy + y) * IMG + ix + 8 * h) * CH + c)
                                                                           : make_uint2(0, 0);
#pragma unroll
          for (int m = 0; m < 6; m++)
            asm("mma.sync.aligned.m16n8k16.row.col.f32.bf16.bf16.f32 {%0,%1,%2,%3}, {%4,%5,%6,%7}, {%8,%9}, {%0,%1,%2,%3};"
                : "+f"(acc[y][m][0]), "+f"(acc[y][m][1]), "+f"(acc[y][m][2]), "+f"(acc[y][m][3])
                : "r"(a[0].x), "r"(a[1].x), "r"(a[0].y), "r"(a[1].y), "r"(b[m][0]), "r"(b[m][1]));
        }
      }
    }
#pragma unroll
    for (int y = 0; y < 4; y++)
#pragma unroll
      for (int m = 0; m < 6; m += 2)
#pragma unroll
        for (int h = 0; h < 2; h++)
          *(uint2*)(out + ((y0 + y) * IMG + x0 + g + 8 * h) * CH + k0 + m * 8 + 4 * t) =
              make_uint2(pack_bf16(acc[y][m][2 * h], acc[y][m + 1][2 * h]), pack_bf16(acc[y][m][2 * h + 1], acc[y][m + 1][2 * h + 1]));
  }
}

struct Descs { uint64_t a[2][6], b[22]; };
__host__ __device__ constexpr int slot_use(int i) {
  int c = 0;
  for (int j = 0; j < i; j++) c += vslot(step_p(j), step_n(j)) == vslot(step_p(i), step_n(i));
  return c;
}

__host__ __device__ constexpr int out_time(int q) {
  constexpr int t[24] = {
      49, 50, 51, 52, 54, 55, 56, 57, 59, 60, 61, 63, 64, 65, 66, 68, 69, 70, 72, 74, 76, 78, 80, 82};
  return t[q];
}
__host__ __device__ constexpr int out_at(int t) {
  for (int q = 0; q < 24; q++)
    if (out_time(q) % NSTEP == t) return q;
  return -1;
}
__host__ __device__ constexpr bool out_ok() {
  for (int q = 0; q < 24; q++)
    if (out_time(q) <= last_on(q / 6) || out_time(q) < PIV + (q < 12 ? 4 : 6) || out_time(q) >= first_on(q / 6) + NSTEP ||
        (q && out_time(q) <= out_time(q - 1)))
      return false;
  return true;
}
static_assert(out_ok(), "output plan");
constexpr int OUT_END = out_time(23) + 1 - NSTEP;

struct Consumer {
  uint32_t c1[48], c2[48], c3[48], c4[48];
  const uint64_t *descA, *descB;
  static constexpr uint32_t sb = SMEM_BASE;
  uint8_t* pout;
  int bid, nblk, nlong;
  uint32_t done;
  uint32_t osc, ymax[2];
  bool lead, ok, odd;

  uint32_t one;
  __device__ __forceinline__ bool always() {
    uint32_t v = one;
    asm volatile("" : "+r"(v));
    return v != 0;
  }
  __device__ __forceinline__ void axpy(uint32_t (&a)[48], uint32_t k, uint32_t (&b)[48]) {
    if (always()) {
      reg_fence(a); reg_fence(b);
#pragma unroll
      for (int i = 0; i < 48; i++) {
        a[i] = hfma2(k, b[i], a[i]);
        if (i % 12 == 11) {
          asm volatile("" : "+r"(a[i])::"memory");
          sched_barrier();
        }
      }
      reg_fence(a);
    }
  }
  uint32_t pa[4], pb[4], px[4];
  __device__ __forceinline__ uint32_t to_bf16(uint32_t h, uint32_t& m) {
    float lo, hi;
    asm("{\n.reg .b16 l, h;\n.reg .b32 m;\nmov.b32 {l, h}, %3;\ncvt.f32.f16 %0, l;\ncvt.f32.f16 %1, h;\n"
        "abs.f16x2 m, %3;\nmax.NaN.f16x2 %2, m, %2;\n}\n" : "=f"(lo), "=f"(hi), "+r"(m) : "r"(h));
    return bmul2(pack_bf16(lo, hi), osc);
  }
  template <int Q, int EXTRA>
  __device__ __forceinline__ void stg(const uint32_t (&v)[4]) {
    constexpr int y = Q < 6 ? 1 : Q < 12 ? 2 : Q < 18 ? 0 : 3;
    asm volatile("st.global.cs.v4.u32 [%0+%5], {%1,%2,%3,%4};" ::"l"(pout), "r"(v[0]), "r"(v[1]), "r"(v[2]), "r"(v[3]),
                 "n"(y * ROWB + (Q / 3) % 2 * 8 * (CH * 2) + Q % 3 * 128 + EXTRA) : "memory");
  }
  template <int Q, bool YIELD>
  __device__ __forceinline__ void convert(uint32_t (&a)[4], uint32_t (&b)[4], uint32_t (&send)[4]) {
    if constexpr (Q >= 0) {
      const uint32_t(&d)[48] = Q < 6 ? c1 : Q < 12 ? c2 : Q < 18 ? c3 : c4;
      constexpr int o = 16 * (Q % 3) + (Q / 3) % 2;
#pragma unroll
      for (int e = 0; e < 4; e++) {
        if (YIELD && e % 2 == 0) sched_barrier();
        a[e] = to_bf16(d[o + 2 * e], ymax[o & 1]);
        b[e] = to_bf16(d[o + 8 + 2 * e], ymax[o & 1]);
        send[e] = odd ? a[e] : b[e];
      }
    }
  }
  template <int QW, int QR, bool STEP>
  __device__ __forceinline__ void output() {
    uint32_t u[4], v[4], a[4], b[4], send[4];
    if constexpr (!STEP) convert<QR, false>(a, b, send);
    sched_barrier();
#pragma unroll
    for (int e = 0; e < 4; e++) {
      u[e] = odd ? px[e] : pa[e];
      v[e] = odd ? pb[e] : px[e];
    }
    if constexpr (STEP) {
      convert<QR, true>(a, b, send);
      asm volatile("{\n.reg .pred p;\nsetp.ne.u32 p, %0, 0;\n@p pmevent 0;\n}" ::"r"((uint32_t)ok) : "memory");
      sched_barrier();
    }
    if constexpr (QW >= 0 && STEP) { stg<QW, 0>(u); stg<QW, CH * 2>(v); }
    if constexpr (QR >= 0) {
#pragma unroll
      for (int e = 0; e < 4; e++) px[e] = __shfl_xor_sync(0xffffffffu, send[e], 4), pa[e] = a[e], pb[e] = b[e];
    }
    if constexpr (QW >= 0 && !STEP) { stg<QW, 0>(u); stg<QW, CH * 2>(v); }
    sched_barrier();
  }
  __device__ __forceinline__ void range_check() {
    sched_barrier();
    uint32_t m = __vmaxu2(__byte_perm(ymax[0], ymax[1], 0x5410), __byte_perm(ymax[0], ymax[1], 0x7632));
    m = __vmaxu2(m, __shfl_xor_sync(0xffffffffu, m, 1));
    m = __vmaxu2(m, __shfl_xor_sync(0xffffffffu, m, 2));
    asm volatile("{\n.reg .pred p;\nsetp.ge.u32 p, %2, %3;\n@p st.shared.u8 [%0], %1;\n}" ::"r"(sb + OFF_REDO + (threadIdx.x & ~31u) + done), "r"(1),
                 "r"(max((m & 0xFFFFu) - Y_MIN, (m >> 16) - Y_MIN)), "n"(Y_INF - Y_MIN) : "memory");
    ymax[0] = ymax[1] = 0;
  }
  template <int T, int Q0, int Q1, int Q = Q0>
  __device__ __forceinline__ void flush() {
    if constexpr (Q <= Q1) {
      constexpr int QW = Q > Q0 && out_time((Q + 23) % 24) >= T - 1 ? Q - 1 : -1, QR = Q < Q1 && out_time(Q % 24) >= T ? Q : -1;
      if constexpr (QW >= 0 || QR >= 0) output<QW, QR, false>();
      flush<T, Q0, Q1, Q + 1>();
    }
  }
  template <int I>
  __device__ __forceinline__ void hook() {
    constexpr float LP = PB * (PB - PA) / (2.f * A2), LM = PB * (PB + PA) / (2.f * A2);
    constexpr int QW = out_at((I + NSTEP - 1) % NSTEP), QR = out_at(I);
    if constexpr (QW >= 0 || QR >= 0) output<QW, QR, true>();
    if constexpr (I == 22) {
      static_assert(OUT_END < NHEAD, "pointer update");
      range_check();
      osc = lds32(sb + OFF_OSC);
      const int r = bid + done * nblk, d = region_px(r) - region_px(r - nblk);
      asm volatile("mad.wide.s32 %0, %1, 384, %0;" : "+l"(pout) : "r"(d));
    }
    if constexpr (I == NHEAD) { if (bid >= nlong && done == 0 && !(bid & 3)) spin_cycles(24500); }
    if constexpr (I == 42) { if (bid >= nlong && done == 0 && (bid & 3)) spin_cycles(28000); }
    if constexpr (I == PIV) axpy(c1, h2const(S3 * (B2 / A2) / S1), c3);
    if constexpr (I == PIV) axpy(c2, h2const(S3 * (B2 / A2) / S2), c3);
    if constexpr (I == PIV + 1) axpy(c4, h2const(-S3 / S4), c3);
    if constexpr (I == PIV + 1) axpy(c1, h2const(S4 * LP / S1), c4);
    if constexpr (I == PIV + 2) axpy(c2, h2const(S4 * LM / S2), c4);
    if constexpr (I == PIV + 2) axpy(c3, h2const(S4 * (-DD / A2)), c4);
    if constexpr (I == PIV + 3) { axpy(c1, h2const(-1.f / (2.f * PA)), c2); axpy(c2, h2const(PA), c1); }
    if constexpr (I == PIV + 4) axpy(c4, h2const(A2), c1);
    if constexpr (I == PIV + 5) axpy(c3, h2const(1.f / A2), c2);
  }

  template <int I, int END, bool FIRST = false>
  __device__ __forceinline__ void steps() {
    if constexpr (I < END) {
      constexpr int J = (I + 1) % NSTEP, S = FIRST ? head(I) : I, T = FIRST ? head(J) : J, G = FIRST ? head_gate_of(I) : gate_of(I);
      uint32_t(&d)[48] = step_acc(S) == 0 ? c1 : step_acc(S) == 1 ? c2 : step_acc(S) == 2 ? c3 : c4;
      constexpr int vo = vslot(step_p(S), step_n(S)) * VSLOT, uo = USLOT<I> * USLAB;
      if (!ok) {
        mbar_wait_short(sb + BAR_UFULL + 8 * USLOT<I>, UUSE<I> & 1);
        if constexpr (first_use(step_n(S)) == S) mbar_wait_short(sb + BAR_VFULL + 8 * (step_n(S) % NB), step_n(S) / NB);
      }
      const uint64_t da = descA[FIRST ? 4 : slot_use(I)], db = descB[(FIRST ? 16 : 0) + UUSE<I>];
      wg_fence();
      wgmma192<vo, uo>(d, da, db, first_on(step_acc(S)) == S ? 0u : 1u);
      wgmma192<vo + 16, uo + UTILE>(d, da, db, 1u);
      wgmma192<vo + 32, uo + 2 * UTILE>(d, da, db, 1u);
      wg_commit();
      ok = mbar_test(sb + BAR_UFULL + 8 * USLOT<J>, UUSE<J> & 1);
      if constexpr (first_use(step_n(T)) == T) ok &= mbar_test(sb + BAR_VFULL + 8 * (step_n(T) % NB), step_n(T) / NB);
      if constexpr (!FIRST) hook<I>();
      wg_wait<0>();
      reg_fence(d);
      if (lead) mbar_arrive(sb + BAR_UEMPTY + 8 * USLOT<I>);
      if constexpr (G >= 0) { if (lead) mbar_arrive(sb + BAR_GATE + 8 * (G % NB)); }
      steps<I + 1, END, FIRST>();
    }
  }
  template <int I>
  __device__ __forceinline__ void chain() {
    if constexpr (I < NSTEP) {
      static_assert(step_acc(I) == 3 && NSTEP - I <= NU, "chain");
      constexpr int vo = vslot(step_p(I), step_n(I)) * VSLOT, uo = USLOT<I> * USLAB;
      mbar_wait_short(sb + BAR_UFULL + 8 * USLOT<I>, UUSE<I> & 1);
      const uint64_t da = descA[5], db = descB[21];
      wg_fence();
      wgmma192<vo, uo>(c4, da, db, 1u);
      wgmma192<vo + 16, uo + UTILE>(c4, da, db, 1u);
      wgmma192<vo + 32, uo + 2 * UTILE>(c4, da, db, 1u);
      wg_commit();
      chain<I + 1>();
    }
  }
  template <int I>
  __device__ __forceinline__ void release() {
    if constexpr (I < NSTEP) {
      if (lead) mbar_arrive(sb + BAR_UEMPTY + 8 * USLOT<I>);
      release<I + 1>();
    }
  }
  template <int T>
  __device__ __forceinline__ void finish(bool second) {
    if (second) {
      flush<T, 0, 18>();
      asm volatile("bar.sync 1, 256;" ::: "memory");
    }
    chain<T>();
    if (!second) {
      asm volatile("bar.arrive 1, 256;" ::: "memory");
      flush<T, 0, 18>();
    }
    wg_wait<0>();
    reg_fence(c4);
    release<T>();
    done++;
    flush<T, 18, 24>();
  }
};

struct SlotTab { uint32_t off[NSUB][8]; };
constexpr SlotTab make_slots() {
  SlotTab t = {};
  for (int n = 0; n < NSUB; n++)
    for (int p = 0; p < 6; p++) t.off[n][p] = vslot(p, n) * VSLOT;
  return t;
}
__constant__ __align__(64) SlotTab c_slots = make_slots();

constexpr int PF_X = 22, PF_BYTES = PF_X * 2 * 16, PF_NB = 12, U_LEAD = 10;
static_assert(PF_BYTES + 64 <= OFF_U - OFF_SINK, "sink");
__host__ __device__ constexpr uint32_t pf_box(int k) { return 1u << 31 | (k / PF_NB / 3) << 30 | (k / PF_NB % 3) << 28 | (k % PF_NB) << 24; }
__host__ __device__ constexpr int slab_of(int i) { return step_p(i % NSTEP) * NSUB + step_n(i % NSTEP); }
struct LoadTab { uint32_t e[2 * NSTEP]; };
constexpr LoadTab make_loads() {
  LoadTab t = {};
  constexpr int win[6] = {25, 42, 45, 72, 73, 96};
  for (int k = 0, i = 0; k < 6 * PF_NB; k++) {
    const int g = k / PF_NB % 3, when = win[2 * g] + k % PF_NB * (win[2 * g + 1] - win[2 * g]) / PF_NB - (k < 3 * PF_NB ? NSTEP : 0);
    if (when >= 0 && when < NSTEP) t.e[NSTEP + when] = pf_box(k);
    if (k < PF_NB) continue;
    if (i < when) i = when;
    if (i < NSTEP) t.e[i++] = pf_box(k);
  }
  for (int i = 0; i < 2 * NSTEP; i++) {
    int d = 1;
    while (uslot((i + d) % NSTEP) != uslot(i % NSTEP)) d++;
    if (d > NU + 1) d = 0;
    t.e[i] |= (uuse(i % NSTEP) & 1) << 23 | uslot(i % NSTEP) << 20 | d << 16 | slab_of(i + U_LEAD) << 8 | slab_of(head(i + d));
  }
  return t;
}
__constant__ __align__(64) LoadTab c_load = make_loads();

template <int I>
__device__ __forceinline__ void first_slabs(const uint8_t* u) {
  if constexpr (utrigger(I) < 0) {
    constexpr int slab = slab_of(head(I));
    load_u_warp(SMEM_BASE + OFF_U + USLOT<I> * USLAB, u + slab * USLAB, SMEM_BASE + BAR_UFULL + 8 * USLOT<I>);
    first_slabs<I + 1>(u);
  }
}

template <int BYTES>
__device__ __forceinline__ uint32_t warm(const void* p, uint32_t zero) {
  uint32_t v = ~0u;
#pragma unroll
  for (int o = 0; o < BYTES; o += 64) v &= ((const uint32_t*)p)[o / 4 + zero];
  return v;
}

__global__ void __launch_bounds__(384, 1) __cluster_dims__(1, 1, 1)
conv_kernel(const __nv_bfloat16* __restrict__ xin, const __nv_bfloat16* __restrict__ wgt, __nv_bfloat16* __restrict__ out, Scratch* scratch,
            int nblk, int nlong, int nmax,
            const __grid_constant__ CUtensorMap tmX, const __grid_constant__ CUtensorMap tmH, const __grid_constant__ CUtensorMap tmP,
            const __grid_constant__ Descs desc) {
  uint4* const ubuf = scratch->u;
  uint32_t* const arrived = scratch->arrived;
  extern __shared__ uint8_t smem_raw[];
  const int tid = threadIdx.x, lane = tid & 31, bid = blockIdx.x;
  const int pidx = bid - (nblk - NP);
  constexpr uint32_t sb = SMEM_BASE;
  uint32_t epoch = 0;
  if (tid < 256) {
    cluster_arrive_relaxed();
    if (pidx >= 0) {
      const uint32_t t0 = pidx * 8 + (tid >> 5), wsm = sb + OFF_V + (tid >> 5) * NROUND * WTASK;
      prep_load(wsm, wgt, t0, lane);
      const Sample ws = sample_w(wgt, lane);
      sched_barrier();
      const float sw = __uint_as_float(max(253 - (int)sample_exp(ws), 0) << 23);
      const int klane = (lane & 6) * 4 + (lane >> 3) * 2 + (lane & 1);
      int stage = 0;
#pragma unroll 1
      for (int round = 0; round < 2 * NROUND; round++) {
        const int k = round < NROUND ? round : round - NROUND;
        asm volatile("cp.async.wait_all;" ::: "memory");
        __syncwarp();
        float g[3][8], gmax = 0.f;
#pragma unroll
        for (int i = 0; i < 24; i++) {
          uint16_t v;
          asm volatile("ld.shared.u16 %0, [%1];" : "=h"(v) : "r"(wsm + k * WTASK + i * 64 + klane * 2) : "memory");
          g[i / 8][i % 8] = __uint_as_float((uint32_t)v << 16);
        }
        if (round >= NROUND) {
#pragma unroll
          for (int i = 0; i < 24; i++) gmax = fmaxf(gmax, fabsf(g[i / 8][i % 8]));
          sched_barrier();
        }
#pragma unroll
        for (int i = 0; i < 24; i++) g[i / 8][i % 8] *= sw;
        if (t0 + k * 8 * NP < NTASK) prep_store(g, gmax > 0.f && gmax * sw < W_MIN, ubuf, t0 + k * 8 * NP, round >= NROUND, klane);
        if (round + 1 == stage_end(0) || round + 1 == stage_end(1) || round + 1 == stage_end(2)) {
          if (++stage == NSTAGE) {
            fence_async();
            asm volatile("ld.relaxed.gpu.global.u32 %0, [%1];" : "=r"(epoch) : "l"(arrived + 32 * NSTAGE) : "memory");
          }
          asm volatile("bar.sync 1, 256;" ::: "memory");
          if (tid == 0)
            asm volatile("red.release.gpu.global.add.u32 [%0], %1;" ::"l"(arrived + 32 * stage), "r"(pidx ? 1 : 0x80000001u - NP) : "memory");
          asm volatile("bar.sync 1, 256;" ::: "memory");
          if (stage == 1) {
#pragma unroll 1
            for (int j = 1; j < NROUND; j++) prep_load(wsm + j * WTASK, wgt, t0 + j * 8 * NP, lane);
          }
        }
      }
      if (tid < 32) asm volatile("bar.arrive 2, 64;" ::: "memory");
    } else if (tid < 32) {
      epoch = stage_enter(arrived, lane, 1);
      spin_until(now(), 2200);
    }
  }
  if (tid >= 352) {
    asm volatile("prefetch.tensormap [%0];" ::"l"(&tmX) : "memory");
    constexpr uint64_t twos = ((2ull << NU) - 1) << (BAR_UEMPTY - OFF_BAR) / 8 | ((1ull << 2 * NB) - 1) << (BAR_VFULL - OFF_BAR) / 8;
    constexpr uint64_t threes = ((1ull << NB) - 1) << (BAR_VFULL - OFF_BAR) / 8;
    if (lane == 0) {
#pragma unroll
      for (int i = 0; i < NBAR; i++) mbar_init(sb + OFF_BAR + 8 * i, 1 + ((twos >> i) & 1) + ((threes >> i) & 1));
      asm volatile("fence.mbarrier_init.release.cluster;" ::: "memory");
      fence_async();
    }
    __syncwarp();
    cluster_arrive_relaxed();
    epoch = stage_enter(arrived, lane, pidx ? 1 : 0x80000001u + NP - 2 * nblk);
    if (pidx >= 0) asm volatile("bar.sync 2, 64;" ::: "memory");
    const uint32_t t0 = now();
#pragma unroll 1
    for (int k = 0, box = 0; k < 9; k++, box = box < 6 ? box + 3 : box - 5) {
      if (pidx < 0) spin_until(t0, min(k, 7) * 410);
      tma_box_warp(sb + OFF_X + box * XBOX, k < 8 ? &tmX : &tmH, sb + BAR_XFULL + 8 * box, k < 8 ? XBOX : XHBOX, 0, halo_x(bid) + k * 8,
                   halo_y(bid));
      if (k == 0) asm volatile("prefetch.tensormap [%0];\nprefetch.tensormap [%1];" ::"l"(&tmH), "l"(&tmP) : "memory");
    }
  }
  if (smem_u32(smem_raw) != SMEM_BASE) __trap();
  const int warp = __shfl_sync(0xffffffffu, tid >> 5, 0);

  if (warp < 8) {
    const int wg = warp >> 2;
    if (warp == 7) {
      spin_until(now(), 1300);
      if ((warm<sizeof(SlotTab)>(&c_slots, tid >> 10) & warm<sizeof(LoadTab)>(&c_load, tid >> 10) & warm<sizeof(Descs)>(&desc, tid >> 10)) == ~0u)
        __trap();
    }
    cluster_wait();
    if (warp == 0) {
      stage_wait(arrived + 32, __shfl_sync(0xffffffffu, epoch, 0));
      first_slabs<0>((const uint8_t*)ubuf);
    }
    asm volatile("setmaxnreg.inc.sync.aligned.u32 224;");
    Consumer c;
#pragma unroll
    for (int i = 0; i < 48; i++) { c.c1[i] = 0; c.c2[i] = 0; c.c3[i] = 0; c.c4[i] = 0; }
#pragma unroll
    for (int e = 0; e < 4; e++) c.pa[e] = c.pb[e] = c.px[e] = 0;
    c.descA = desc.a[wg];
    c.descB = desc.b;
    c.lead = (tid & 127) == 0;
    c.one = __shfl_sync(0xffffffffu, nblk, 0);
    c.ok = false;
    c.bid = bid;
    c.nblk = nblk;
    c.nlong = nlong;
    c.odd = (lane >> 2) & 1;
    c.pout = (uint8_t*)out + (long long)(region_px(bid - nblk) + wg * 4 * IMG + (warp & 3) * 16 + (lane >> 3) * 2) * (CH * 2) + (lane & 7) * 16;
    c.done = c.osc = c.ymax[0] = c.ymax[1] = 0;
    asm volatile("st.shared.u8 [%0], %1;" ::"r"(sb + OFF_REDO + tid), "r"(0) : "memory");
    constexpr int ROT = 69;
    c.steps<0, NHEAD, true>();
    bool tail = false;
#pragma unroll 1
    do {
      wg_wait<0>();
      if (tail) {
        c.steps<ROT, NSTEP>();
        c.done++;
        c.steps<0, NHEAD>();
      }
      c.steps<NHEAD, ROT>();
      tail = c.always();
    } while (bid + (int)(c.done + 1) * nblk < NREG);
    c.finish<ROT>(wg);
    c.range_check();
    __syncwarp();
    uint32_t redo;
    asm volatile("ld.shared.u8 %0, [%1];" : "=r"(redo) : "r"(sb + OFF_REDO + tid) : "memory");
    redo = __ballot_sync(0xffffffffu, redo) >> 1;
    if (redo) {
      for (int i = 0; i < (int)c.done; i++)
        if ((redo >> i) & 1) {
          const int r = bid + i * nblk;
          direct_patch(xin, wgt, out, (r >> 3) * 8 + wg * 4, (r & 7) * 64 + (warp & 3) * 16, lane);
        }
    }
  } else {
    asm volatile("setmaxnreg.dec.sync.aligned.u32 56;");
    const int nitem = nmax - (bid >= nlong);
    if (warp == 11) {
      const uint8_t* ubase = (const uint8_t*)ubuf;
      epoch = __shfl_sync(0xffffffffu, epoch, 0);
      cluster_wait();
      const uint8_t* uline = ubase + (bid * 2 + lane) * 128;
      const bool ufetch = lane < 2 && bid < USLAB / 256;
      int r = bid, npf = 0, i = 0, tab = 0;
#pragma unroll 1
      for (int left = nitem * NSTEP - 1; left >= 0; left--) {
        const uint32_t e = c_load.e[tab + i], slot = (e >> 20) & 7;
        const uint8_t* src = ubase + (e & 255) * USLAB;
        const uint8_t* pu = uline + ((e >> 8) & 255) * USLAB;
        const uint32_t dst = sb + OFF_U + slot * USLAB, ebar = sb + BAR_UEMPTY + 8 * slot;
        const bool refill = ((e >> 16) & 7) - 1 < (uint32_t)left;
        constexpr int need1 = utrigger(stage_first(1)), need2 = utrigger(stage_first(2)), xslab = slab_of(UX_FIRST);
        if (tab + i == need1 || tab + i == need2) stage_wait(arrived + (i == need1 ? 64 : 96), epoch);
        refill_u(ebar, (e >> 23) & 1, refill, dst, src);
        if (i == UX_GATE) load_u_warp(sb + OFF_V, ubase + xslab * USLAB, sb + BAR_UFULL + 8 * NU);
        const int rr = r + ((e >> 30) & 1) * nblk;
        if ((int)e < 0 && rr < NREG) {
          asm volatile("{\n.reg .pred p;\nelect.sync _|p, 0xffffffff;\n"
                       "@p cp.async.bulk.tensor.3d.shared::cluster.global.mbarrier::complete_tx::bytes [%0], [%1, {%3, %4, %5}], [%2];\n}\n"
                       ::"r"(sb + OFF_SINK), "l"(&tmP), "r"(sb + BAR_SINK), "r"((e >> 22) & 0xC0), "r"(halo_x(rr) + ((e >> 26) & 3) * PF_X),
                       "r"(halo_y(rr) + 1 + ((e >> 23) & 6)) : "memory");
          npf++;
        }
        if (ufetch && tab + i >= NSTEP - U_LEAD && left >= U_LEAD)
          asm volatile("cp.async.ca.shared.global.L2::128B [%0], [%1], 4;" ::"r"(sb + OFF_SINK + PF_BYTES + lane * 4), "l"(pu) : "memory");
        if (++i == NSTEP) { i = 0; r += nblk; tab = NSTEP; }
      }
      if (lane == 0) asm volatile("mbarrier.arrive.expect_tx.shared::cta.b64 _, [%0], %1;" ::"r"(sb + BAR_SINK), "r"(npf * PF_BYTES) : "memory");
      mbar_wait(sb + BAR_SINK, 0);
      asm volatile("cp.async.wait_all;" ::: "memory");
    } else {
      cluster_arrive_relaxed();
      const int w = warp - 8, col = (lane >> 1) & 7, chunk = lane >> 4;
      const uint32_t xbox = sb + OFF_X + w * 3 * XBOX, xbar = sb + BAR_XFULL + 24 * w;
      const uint32_t xl = xbox + col * 32 + ((chunk ^ (col >> 2)) << 4) + (lane & 1) * 8;
      const uint32_t vl = sb + OFF_V + chunk * VROW + w * 128 + (lane & 15) * 8;
      const bool in_row = w < 2 || col < 2;
      const uint32_t pitch2 = w < 2 ? 256 : 64, bytes2 = 10 * pitch2;
      const uint32_t xl2 = w < 2 ? xl + 2 * XBOX : xbox + 2 * XBOX + col * 32 + chunk * 16 + (lane & 1) * 8;
      const CUtensorMap* tm2 = w < 2 ? &tmX : &tmH;
      auto xrow = [&](int j, int i) {
        uint2 v = make_uint2(0, 0);
        if (j < 2 || in_row) v = lds64(j < 2 ? xl + j * XBOX + i * 256 : xl2 + i * pitch2);
        return v;
      };
      const Sample ws = sample_w(wgt, lane), xs = sample_x(xin, bid, lane);
      uint32_t xsc;
      {
        const int ex = sample_exp(xs), eo = ex + (int)sample_exp(ws) - (111 + X_EXP), es = 127 + X_EXP - ex;
        xsc = es >= 1 && eo >= 1 && eo <= 254 ? es * 0x00800080u : NAN2;
        asm volatile("st.shared.u32 [%0], %1;" ::"r"(sb + OFF_OSC), "r"(eo * 0x00800080u) : "memory");
      }
      constexpr uint32_t gate_par = [] {
        uint32_t m = 0;
        for (int n = 0; n < NSUB; n++) m |= (uint32_t)((n / NB) ^ (gate(n % NB) < 0)) << n;
        return m;
      }();
      constexpr uint32_t LIM2 = X_LIM * 0x10001u;
      cluster_wait();
      auto conv = [&](uint2& v, uint32_t m) {
        const uint32_t tx = bmul2(v.x, xsc), ty = bmul2(v.y, xsc), ux = tx & NAN2, uy = ty & NAN2;
        v = make_uint2(ux * 7 + tx, uy * 7 + ty);
        return __vimax3_u16x2(m, ux, uy);
      };
      uint32_t so[6] = {};
      auto planes = [&](const uint2* h, uint32_t m, uint32_t a, bool on) {
        constexpr uint32_t NB2 = h2const(-B2), NA2 = h2const(-A2);
        const uint2 e1 = fma4(NB2, h[2], h[4]), e2 = fma4(NA2, h[2], h[4]);
        store_v(a + so[4], fma4(NA2, fma4(NB2, h[0], h[2]), e1), on);
        const uint2 o1 = fma4(NB2, h[1], h[3]), o2 = fma4(NA2, h[1], h[3]);
        store_v(a + so[5], fma4(NA2, o1, fma4(NB2, h[3], h[5])), on);
        uint2 v = fma4(h2const(PA), o1, e1);
        if (m != LIM2) v.x = NAN2;
        store_v(a + so[0], v, on);
        store_v(a + so[1], fma4(h2const(-PA), o1, e1), on);
        store_v(a + so[2], fma4(h2const(PB), o2, e2), on);
        store_v(a + so[3], fma4(h2const(-PB), o2, e2), on);
      };
      int r = bid, n = 0;
      uint32_t par = 0;
#pragma unroll 1
      for (int left = nitem * NSUB; left > 0; left--) {
        const int nb = n >= NB ? n - NB : n;
        uint2 d[10];
        mbar_wait(xbar, par);
#pragma unroll
        for (int i = 0; i < 6; i++) d[i] = xrow(0, i);
#pragma unroll
        for (int p = 0; p < 6; p++) so[p] = c_slots.off[n][p];
        const uint32_t gpar = (gate_par >> n) & 1;
        if (++n == NSUB) { n = 0; r += nblk; }
        const int fc = n * 16, fx = halo_x(r) + w * 8, fy = halo_y(r);
#pragma unroll
        for (int j = 0; j < 3; j++) {
          const bool on = j < 2 || in_row;
#pragma unroll
          for (int i = 6; i < 10; i++) d[i] = xrow(j, i);
          const bool xok = j < 2 && mbar_test(xbar + 8 * (j + 1), par);
          sched_barrier();
          const uint32_t m45 = conv(d[5], conv(d[4], LIM2));
          const uint32_t ma = conv(d[3], conv(d[1], conv(d[0], conv(d[2], m45))));
          if (j == 0) mbar_wait(sb + BAR_GATE + 8 * nb, gpar);
          planes(d, ma, vl + j * 384, on);
          sched_barrier();
          const uint32_t mb = conv(d[9], conv(d[7], conv(d[6], conv(d[8], m45))));
          if (left > 1)
            tma_box_warp(xbox + j * XBOX, j < 2 ? &tmX : tm2, xbar + 8 * j, (j < 2 ? XBOX : bytes2) | (mb & 0x8000u), fc, fx + j * 24, fy);
          uint2 h[6];
#pragma unroll
          for (int i = 0; i < 6; i++) h[i] = d[4 + i];
          if (j < 2) {
            mbar_wait(xbar + 8 * (j + 1), par, xok);
#pragma unroll
            for (int i = 0; i < 6; i++) d[i] = xrow(j + 1, i);
          }
          sched_barrier();
          planes(h, mb, vl + j * 384 + VPIECE, on);
          sched_barrier();
        }
        fence_async();
        asm volatile("{\n.reg .pred p;\nelect.sync _|p, 0xffffffff;\n@p mbarrier.arrive.shared::cta.b64 _, [%0];\n}\n"
                     ::"r"(sb + BAR_VFULL + 8 * nb) : "memory");
        par ^= 1;
      }
    }
  }
}

constexpr uint64_t make_desc(uint32_t off, uint32_t lbo, uint32_t sbo) {
  return (uint64_t)((SMEM_BASE + off) >> 4) | ((uint64_t)(lbo >> 4) << 16) | ((uint64_t)(sbo >> 4) << 32);
}

typedef CUresult (*EncodeFn)(CUtensorMap*, CUtensorMapDataType, cuuint32_t, void*, const cuuint64_t*, const cuuint64_t*,
                             const cuuint32_t*, const cuuint32_t*, CUtensorMapInterleave, CUtensorMapSwizzle,
                             CUtensorMapL2promotion, CUtensorMapFloatOOBfill);

}

extern "C" void kernel_launch(void* const* d_in, const int* in_sizes, int n_in, void* d_out, int out_size) {
  static EncodeFn enc = nullptr;
  static int nblk = 0;
  static Scratch* scratch;
  if (!enc) {
    cudaGetSymbolAddress((void**)&scratch, g_scratch);
    cudaDriverEntryPointQueryResult qr;
    cudaGetDriverEntryPoint("cuTensorMapEncodeTiled", (void**)&enc, cudaEnableDefault, &qr);
    cudaFuncSetAttribute(conv_kernel, cudaFuncAttributeMaxDynamicSharedMemorySize, SMEM_BYTES);
    int dev;
    cudaGetDevice(&dev);
    cudaDeviceGetAttribute(&nblk, cudaDevAttrMultiProcessorCount, dev);
  }
  CUtensorMap tmX, tmH, tmP;
  const cuuint64_t dims[3] = {CH, IMG, IMG};
  const cuuint64_t strides[2] = {CH * 2, (cuuint64_t)CH * 2 * IMG};
  const cuuint32_t es[3] = {1, 1, 1};
  const cuuint32_t boxX[3] = {16, 8, 10}, boxH[3] = {16, 2, 10}, boxP[3] = {8, PF_X, 2};
  enc(&tmH, CU_TENSOR_MAP_DATA_TYPE_BFLOAT16, 3, d_in[0], dims, strides, boxH, es, CU_TENSOR_MAP_INTERLEAVE_NONE,
      CU_TENSOR_MAP_SWIZZLE_NONE, CU_TENSOR_MAP_L2_PROMOTION_L2_64B, CU_TENSOR_MAP_FLOAT_OOB_FILL_NONE);
  enc(&tmP, CU_TENSOR_MAP_DATA_TYPE_BFLOAT16, 3, d_in[0], dims, strides, boxP, es, CU_TENSOR_MAP_INTERLEAVE_NONE,
      CU_TENSOR_MAP_SWIZZLE_NONE, CU_TENSOR_MAP_L2_PROMOTION_L2_128B, CU_TENSOR_MAP_FLOAT_OOB_FILL_NONE);
  enc(&tmX, CU_TENSOR_MAP_DATA_TYPE_BFLOAT16, 3, d_in[0], dims, strides, boxX, es, CU_TENSOR_MAP_INTERLEAVE_NONE,
      CU_TENSOR_MAP_SWIZZLE_32B, CU_TENSOR_MAP_L2_PROMOTION_L2_64B, CU_TENSOR_MAP_FLOAT_OOB_FILL_NONE);
  Descs desc = {};
  for (int i = 0; i < 6; i++) { desc.a[0][i] = make_desc(OFF_V, VROW, 128); desc.a[1][i] = make_desc(OFF_V + VPIECE, VROW, 128); }
  for (int i = 0; i < 22; i++) desc.b[i] = make_desc(OFF_U, 128, 256);
  conv_kernel<<<nblk, 384, SMEM_BYTES>>>((const __nv_bfloat16*)d_in[0], (const __nv_bfloat16*)d_in[1], (__nv_bfloat16*)d_out, scratch, nblk,
                                         NREG % nblk ? NREG % nblk : nblk, (NREG + nblk - 1) / nblk, tmX, tmH, tmP, desc);
}
```

```cpp
#include <cuda_runtime.h>
#include <cuda_bf16.h>
#include <cuda.h>
#include <stdint.h>

namespace {

constexpr int IMG = 512, CH = 192;
constexpr float PA = 1.5f, PB = 0.6875f;
constexpr float A2 = PA * PA, B2 = PB * PB, DD = B2 - A2;

constexpr int NSTEP = 72, NSUB = 12;
__host__ __device__ constexpr int sched(int i) {
  constexpr int t[NSTEP] = {
      0x00, 0x10, 0x20, 0x01, 0x11, 0x21, 0x02, 0x12, 0x22, 0x03, 0x13, 0x23, 0x30, 0x31, 0x32, 0x33, 0x24, 0x34,
      0x04, 0x14, 0x25, 0x35, 0x05, 0x15, 0x26, 0x36, 0x06, 0x16, 0x27, 0x37, 0x07, 0x17, 0x28, 0x38, 0x08, 0x18,
      0x29, 0x39, 0x09, 0x19, 0x2a, 0x3a, 0x0a, 0x1a, 0x2b, 0x3b, 0x1b, 0x0b, 0x40, 0x4b, 0x50, 0x41, 0x51, 0x4a,
      0x49, 0x48, 0x47, 0x42, 0x52, 0x46, 0x45, 0x5b, 0x44, 0x43, 0x5a, 0x53, 0x59, 0x58, 0x57, 0x56, 0x54, 0x55};
  return t[i];
}
__host__ __device__ constexpr int step_p(int i) { return sched(i) >> 4; }
__host__ __device__ constexpr int step_n(int i) { return sched(i) & 15; }
__host__ __device__ constexpr int step_acc(int i) { return step_p(i) < 4 ? step_p(i) : step_p(i) - 2; }
__host__ __device__ constexpr int first_on(int acc) {
  for (int i = 0; i < NSTEP; i++)
    if (step_acc(i) == acc) return i;
  return -1;
}
__host__ __device__ constexpr int last_on(int acc) {
  for (int i = NSTEP - 1; i >= 0; i--)
    if (step_acc(i) == acc) return i;
  return -1;
}
__host__ __device__ constexpr int find_step(int p, int n) {
  for (int i = 0; i < NSTEP; i++)
    if (sched(i) == p * 16 + n) return i;
  return -1;
}
__host__ __device__ constexpr int first_use(int n) {
  for (int i = 0; i < NSTEP; i++)
    if (step_n(i) == n) return i;
  return -1;
}
constexpr int NHEAD = first_on(3) / 3 * 4;
__host__ __device__ constexpr int head(int i) { return i < NHEAD ? find_step(i % 4, i / 4) : i; }
constexpr float S1 = 1.f / PA, S2 = 1.f / (2.f * A2), S3 = -A2 / (2.f * DD), S4 = -1.f / (PB * DD);
constexpr int PIV = find_step(3, NSUB - 1);
static_assert(find_step(2, NSUB - 1) == PIV - 1 && last_on(1) == PIV + 1 && last_on(0) == PIV + 2 && PIV + 3 == 4 * NSUB &&
              step_p(PIV + 3) == 4 && step_p(PIV + 4) == 4 && step_p(PIV + 5) == 5, "basis change");

constexpr int NV = 32, NB = 6;
__host__ __device__ constexpr int vslot(int p, int n) {
  constexpr int t[6][NSUB] = {
      {31, 19, 25, 18, 19, 27, 21, 4, 24, 26, 3, 26}, {28, 23, 24, 22, 17, 24, 28, 3, 25, 27, 0, 28},
      {27, 17, 14, 20, 23, 22, 20, 31, 0, 28, 1, 2}, {26, 21, 15, 16, 31, 18, 23, 26, 23, 31, 4, 31},
      {7, 6, 8, 10, 12, 14, 15, 17, 19, 21, 23, 27}, {30, 29, 9, 11, 13, 5, 16, 18, 20, 22, 24, 25}};
  return t[p][n];
}
__host__ __device__ constexpr int gate(int n) {
  constexpr int t[NSUB] = {-20, -14, -8, -2, 5, 11, 16, 21, 25, 29, 34, 39};
  return t[n];
}
__host__ __device__ constexpr int gate_of(int i) {
  for (int n = 0; n < NSUB; n++)
    if ((gate(n) + NSTEP) % NSTEP == i) return n;
  return -1;
}
__host__ __device__ constexpr int head_gate_of(int i) {
  for (int n = 0; n < NSUB; n++) {
    int m = -1;
    for (int j = 0; j < NHEAD; j++)
      if (head(j) <= gate(n)) m = j;
    if (gate(n) < NHEAD && m == i) return n;
  }
  return -1;
}
__host__ __device__ constexpr bool gates_ok() {
  int early = 0;
  for (int i = 0; i < NHEAD; i++) early += (gate_of(i) >= 0) - (head_gate_of(i) >= 0) + (head(i) >= NHEAD);
  if (early) return false;
  for (int n = 0; n < NSUB; n++) {
    for (int p = 0; p < 6; p++)
      for (int d = 1; d <= NSUB; d++)
        for (int q = 0; q < 6; q++) {
          const int m = (n - d + NSUB) % NSUB;
          if (vslot(q, m) == vslot(p, n) && (find_step(q, m) - (n - d < 0 ? NSTEP : 0) > gate(n) || (m == n && p != q))) return false;
        }
    if (n > 0 && (gate(n) <= gate(n - 1) || first_use(n) <= first_use(n - 1))) return false;
    if (gate(n) >= first_use(n)) return false;
    if (gate((n + NB) % NSUB) + (n >= NB ? NSTEP : 0) < first_use(n)) return false;
  }
  return gate(0) + NSTEP > gate(NSUB - 1) && gate(NB) >= 0;
}
static_assert(gates_ok(), "gates");

constexpr int UTILE = CH * 16 * 2;
constexpr int USLAB = 3 * UTILE;
constexpr int NU = 4;
constexpr int VROW = 66 * 16;
constexpr int VPIECE = 2 * VROW;
constexpr int VSLOT = 2 * VPIECE;
constexpr int XBOX = 10 * 8 * 32;
constexpr int XHBOX = 10 * 2 * 32;
constexpr int UX_FIRST = 52, UX_COUNT = 8, UX_GATE = UX_FIRST - NU - 1;
__host__ __device__ constexpr bool uextra(int i) {
  const int d = (i - UX_FIRST + NSTEP) % NSTEP;
  return d % (NU + 1) == 0 && d / (NU + 1) < UX_COUNT;
}
__host__ __device__ constexpr int uindex(int i) {
  int c = 0;
  for (int j = 0; j < i; j++) c += uextra(j) == uextra(i);
  return c;
}
__host__ __device__ constexpr int uslot(int i) { return uextra(i) ? NU : uindex(i) % NU; }
__host__ __device__ constexpr int uuse(int i) { return uextra(i) ? uindex(i) : uindex(i) / NU; }
__host__ __device__ constexpr int utrigger(int j) {
  if (j == UX_FIRST) return UX_GATE;
  int i = j - 1;
  while (uslot((i + NSTEP) % NSTEP) != uslot(j)) i--;
  return i;
}
template <int I> constexpr int USLOT = uslot(I);
template <int I> constexpr int UUSE = uuse(I);
__host__ __device__ constexpr bool uring_ok() {
  for (int n = 0; n < NSUB; n++)
    for (int p = 0; p < 6; p++)
      if (vslot(p, n) * VSLOT < USLAB && (find_step(p, n) > UX_GATE || gate(n) < UX_FIRST + (NU + 1) * (UX_COUNT - 1) - NSTEP))
        return false;
  return UX_COUNT % 2 == 0 && (NSTEP - UX_COUNT) % (2 * NU) == 0;
}
static_assert(uring_ok(), "U ring");

constexpr int OFF_X = 0;
constexpr int OFF_U = OFF_X + 8 * XBOX + XHBOX;
constexpr int OFF_V = OFF_U + NU * USLAB;
constexpr int OFF_BAR = OFF_V + NV * VSLOT;
constexpr int BAR_UFULL = OFF_BAR;
constexpr int BAR_UEMPTY = BAR_UFULL + 8 * (NU + 1);
constexpr int BAR_XFULL = BAR_UEMPTY + 8 * (NU + 1);
constexpr int BAR_VFULL = BAR_XFULL + 8 * 9;
constexpr int BAR_GATE = BAR_VFULL + 8 * NB;
constexpr int OFF_OSC = BAR_GATE + 8 * NB;
constexpr int NBAR = (OFF_OSC - OFF_BAR) / 8;
constexpr int OFF_REDO = OFF_OSC + 8;
constexpr int SMEM_BYTES = OFF_REDO + 256;
constexpr uint32_t SMEM_BASE = 1024;
static_assert(SMEM_BYTES <= 232448, "smem");

constexpr int NREG = 512;

struct Scratch {
  uint4 u[NSTEP * USLAB / 16];
  uint32_t arrived[4 * 32];
};
__device__ __align__(128) Scratch g_scratch;

__device__ __forceinline__ uint32_t smem_u32(const void* p) { return (uint32_t)__cvta_generic_to_shared(p); }
__device__ __forceinline__ void mbar_init(uint32_t a, int c) {
  asm volatile("mbarrier.init.shared::cta.b64 [%0], %1;" ::"r"(a), "r"(c) : "memory");
}
__device__ __forceinline__ void mbar_arrive(uint32_t a) {
  asm volatile("mbarrier.arrive.shared::cta.b64 _, [%0];" ::"r"(a) : "memory");
}
__device__ __forceinline__ void mbar_wait(uint32_t a, uint32_t parity, uint32_t skip = 0) {
  asm volatile(
      "{\n"
      ".reg .pred p;\n"
      ".reg .u32 n;\n"
      "setp.ne.u32 p, %2, 0;\n"
      "@p bra.uni LAB_DONE;\n"
      "mov.u32 n, 0;\n"
      "LAB_WAIT:\n"
      "mbarrier.try_wait.parity.shared::cta.b64 p, [%0], %1;\n"
      "@p bra.uni LAB_DONE;\n"
      "add.u32 n, n, 1;\n"
      "setp.lt.u32 p, n, 4000000;\n"
      "@p bra.uni LAB_WAIT;\n"
      "trap;\n"
      "LAB_DONE:\n"
      "}\n" ::"r"(a), "r"(parity), "r"(skip) : "memory");
}
__device__ __forceinline__ void mbar_wait_short(uint32_t a, uint32_t parity) {
  asm volatile("{\n.reg .pred p;\nLAB_WAIT:\nmbarrier.try_wait.parity.shared::cta.b64 p, [%0], %1;\n@!p bra.uni LAB_WAIT;\n}\n" ::"r"(a),
               "r"(parity) : "memory");
}
__device__ __forceinline__ bool mbar_test(uint32_t a, uint32_t parity) {
  uint32_t ok;
  asm volatile("{\n.reg .pred p;\nmbarrier.test_wait.parity.shared::cta.b64 p, [%1], %2;\nselp.u32 %0, 1, 0, p;\n}\n"
               : "=r"(ok) : "r"(a), "r"(parity) : "memory");
  return ok;
}
__device__ __forceinline__ void fence_async() { asm volatile("fence.proxy.async.shared::cta;" ::: "memory"); }
__device__ __forceinline__ void tma_box_warp(uint32_t dst, const CUtensorMap* tm, uint32_t bar, uint32_t bytes, int c, int x, int y) {
  asm volatile(
      "{\n.reg .pred p;\nelect.sync _|p, 0xffffffff;\n"
      "@p mbarrier.arrive.expect_tx.shared::cta.b64 _, [%2], %6;\n"
      "@p cp.async.bulk.tensor.3d.shared::cluster.global.mbarrier::complete_tx::bytes [%0], [%1, {%3, %4, %5}], [%2];\n}\n" ::"r"(dst),
      "l"(tm), "r"(bar), "r"(c), "r"(x), "r"(y), "r"(bytes) : "memory");
}
__device__ __forceinline__ void load_u_warp(uint32_t dst, const void* src, uint32_t bar) {
  asm volatile("{\n.reg .pred p;\nelect.sync _|p, 0xffffffff;\n"
               "@p mbarrier.arrive.expect_tx.shared::cta.b64 _, [%2], %3;\n"
               "@p cp.async.bulk.shared::cluster.global.mbarrier::complete_tx::bytes [%0], [%1], %3, [%2];\n}\n" ::"r"(dst),
               "l"(src), "r"(bar), "n"(USLAB) : "memory");
}
__device__ __forceinline__ void refill_u(uint32_t ebar, uint32_t parity, uint32_t on, uint32_t dst, const void* src) {
  asm volatile(
      "{\n.reg .pred p;\n.reg .u32 n;\n"
      "mov.u32 n, 0;\n"
      "LAB_WAIT:\n"
      "mbarrier.try_wait.parity.shared::cta.b64 p, [%0], %1;\n"
      "@p bra.uni LAB_DONE;\n"
      "add.u32 n, n, 1;\nsetp.lt.u32 p, n, 4000000;\n"
      "@p bra.uni LAB_WAIT;\n"
      "trap;\n"
      "LAB_DONE:\n"
      "setp.eq.u32 p, %2, 0;\n"
      "@p bra.uni LAB_OUT;\n"
      "elect.sync _|p, 0xffffffff;\n"
      "@p mbarrier.arrive.expect_tx.shared::cta.b64 _, [%5], %6;\n"
      "@p cp.async.bulk.shared::cluster.global.mbarrier::complete_tx::bytes [%3], [%4], %6, [%5];\n"
      "LAB_OUT:\n}\n" ::"r"(ebar), "r"(parity), "r"(on), "r"(dst), "l"(src), "r"(ebar - (BAR_UEMPTY - BAR_UFULL)), "n"(USLAB) : "memory");
}
__device__ __forceinline__ uint2 lds64(uint32_t a) {
  uint2 v;
  asm volatile("ld.shared.v2.u32 {%0,%1}, [%2];" : "=r"(v.x), "=r"(v.y) : "r"(a) : "memory");
  return v;
}
__device__ __forceinline__ uint32_t lds32(uint32_t a) {
  uint32_t v;
  asm volatile("ld.shared.u32 %0, [%1];" : "=r"(v) : "r"(a) : "memory");
  return v;
}
__device__ __forceinline__ void store_v(uint32_t a, uint2 v, bool on) {
  v.x &= 0xFFFCFFFCu; v.y &= 0xFFFCFFFCu;
  if (on) asm volatile("st.shared.v2.u32 [%0], {%1,%2};" ::"r"(a), "r"(v.x), "r"(v.y) : "memory");
}
__device__ __forceinline__ void sched_barrier() { asm volatile("pmevent 0;" ::: "memory"); }
__device__ __forceinline__ void spin_cycles(uint32_t n) {
  asm volatile(
      "{\n.reg .pred p;\n.reg .u32 t0, t;\n"
      "mov.u32 t0, %%clock;\n"
      "LAB_SPIN:\n"
      "nanosleep.u32 50;\n"
      "mov.u32 t, %%clock;\nsub.u32 t, t, t0;\nsetp.lt.u32 p, t, %0;\n"
      "@p bra.uni LAB_SPIN;\n}\n" ::"r"(n) : "memory");
}
__device__ __forceinline__ void spin_until(uint32_t t0, uint32_t n) {
  asm volatile("{\n.reg .pred p;\n.reg .u32 t;\nLAB_SPIN:\nmov.u32 t, %%clock;\nsub.u32 t, t, %0;\nsetp.lt.u32 p, t, %1;\n"
               "@p bra.uni LAB_SPIN;\n}\n" ::"r"(t0), "r"(n) : "memory");
}
__device__ __forceinline__ uint32_t now() {
  uint32_t t;
  asm volatile("mov.u32 %0, %%clock;" : "=r"(t)::"memory");
  return t;
}
__device__ __forceinline__ uint32_t stage_enter(uint32_t* ctr, int lane, uint32_t inc) {
  uint32_t old;
  asm volatile("{\n.reg .pred p;\nsetp.eq.u32 p, %2, 0;\nld.relaxed.gpu.global.u32 %0, [%1];\n@p red.relaxed.gpu.global.add.u32 [%1], %3;\n}"
               : "=r"(old) : "l"(ctr), "r"(lane), "r"(inc) : "memory");
  return old;
}
__device__ __forceinline__ void stage_wait(const uint32_t* ctr, uint32_t old) {
  asm volatile(
      "{\n.reg .pred p;\n.reg .u32 v, i;\n"
      "mov.u32 i, 0;\n"
      "LAB_POLL:\n"
      "ld.acquire.gpu.global.u32 v, [%0];\n"
      "xor.b32 v, v, %1;\nsetp.lt.s32 p, v, 0;\n"
      "@p bra.uni LAB_OUT;\n"
      "add.u32 i, i, 1;\nsetp.lt.u32 p, i, 4000000;\n"
      "@p bra.uni LAB_POLL;\n"
      "trap;\n"
      "LAB_OUT:\n"
      "fence.proxy.async.global;\n}\n" ::"l"(ctr), "r"(old) : "memory");
}
__device__ __forceinline__ void cluster_arrive_relaxed() { asm volatile("barrier.cluster.arrive.relaxed.aligned;" ::: "memory"); }
__device__ __forceinline__ void cluster_wait() { asm volatile("barrier.cluster.wait.acquire.aligned;" ::: "memory"); }

__host__ __device__ constexpr uint32_t h2const(float v) {
  double a = v < 0 ? -v : v;
  int e = 15;
  while (a >= 2) { a /= 2; e++; }
  while (a < 1) { a *= 2; e--; }
  const uint32_t h = (v < 0 ? 0x8000u : 0u) | ((e << 10) + (uint32_t)((a - 1) * 1024 + 0.5));
  return h | h << 16;
}
__device__ __forceinline__ uint32_t hfma2(uint32_t a, uint32_t b, uint32_t c) {
  uint32_t d;
  asm("fma.rn.f16x2 %0, %1, %2, %3;" : "=r"(d) : "r"(a), "r"(b), "r"(c));
  return d;
}
__device__ __forceinline__ uint32_t bmul2(uint32_t a, uint32_t b) {
  uint32_t d;
  asm("mul.rn.bf16x2 %0, %1, %2;" : "=r"(d) : "r"(a), "r"(b));
  return d;
}
__device__ __forceinline__ uint2 fma4(uint32_t k, const uint2& a, const uint2& c) { return make_uint2(hfma2(k, a.x, c.x), hfma2(k, a.y, c.y)); }
__device__ __forceinline__ uint32_t pack_bf16(float lo, float hi) {
  uint32_t d;
  asm("cvt.rn.bf16x2.f32 %0, %1, %2;" : "=r"(d) : "f"(hi), "f"(lo));
  return d;
}
__device__ __forceinline__ uint32_t pack_f16(float lo, float hi) {
  uint32_t d;
  asm("cvt.rn.f16x2.f32 %0, %1, %2;" : "=r"(d) : "f"(hi), "f"(lo));
  return d;
}

template <int AOFF, int BOFF>
__device__ __forceinline__ void wgmma192(uint32_t (&d)[48], uint64_t da, uint64_t db, uint32_t scale_d) {
  asm volatile(
      "{\n.reg .pred p;\n.reg .b64 qa, qb;\n"
      "setp.ne.b32 p, %50, 0;\n"
      "add.s64 qa, %48, %51;\nadd.s64 qb, %49, %52;\n"
      "wgmma.mma_async.sync.aligned.m64n192k16.f16.f16.f16 "
      "{%0, %1, %2, %3, %4, %5, %6, %7, %8, %9, %10, %11, %12, %13, %14, %15, "
      "%16, %17, %18, %19, %20, %21, %22, %23, %24, %25, %26, %27, %28, %29, %30, %31, "
      "%32, %33, %34, %35, %36, %37, %38, %39, %40, %41, %42, %43, %44, %45, %46, %47}, "
      "qa, qb, p, 1, 1, 0, 0;\n}\n"
      : "+r"(d[0]), "+r"(d[1]), "+r"(d[2]), "+r"(d[3]), "+r"(d[4]), "+r"(d[5]), "+r"(d[6]), "+r"(d[7]), "+r"(d[8]),
        "+r"(d[9]), "+r"(d[10]), "+r"(d[11]), "+r"(d[12]), "+r"(d[13]), "+r"(d[14]), "+r"(d[15]), "+r"(d[16]),
        "+r"(d[17]), "+r"(d[18]), "+r"(d[19]), "+r"(d[20]), "+r"(d[21]), "+r"(d[22]), "+r"(d[23]), "+r"(d[24]),
        "+r"(d[25]), "+r"(d[26]), "+r"(d[27]), "+r"(d[28]), "+r"(d[29]), "+r"(d[30]), "+r"(d[31]), "+r"(d[32]),
        "+r"(d[33]), "+r"(d[34]), "+r"(d[35]), "+r"(d[36]), "+r"(d[37]), "+r"(d[38]), "+r"(d[39]), "+r"(d[40]),
        "+r"(d[41]), "+r"(d[42]), "+r"(d[43]), "+r"(d[44]), "+r"(d[45]), "+r"(d[46]), "+r"(d[47])
      : "l"(da), "l"(db), "r"(scale_d), "n"(AOFF >> 4), "n"(BOFF >> 4));
}
__device__ __forceinline__ void wg_fence() { asm volatile("wgmma.fence.sync.aligned;" ::: "memory"); }
__device__ __forceinline__ void wg_commit() { asm volatile("wgmma.commit_group.sync.aligned;" ::: "memory"); }
template <int N>
__device__ __forceinline__ void wg_wait() { asm volatile("wgmma.wait_group.sync.aligned %0;" ::"n"(N) : "memory"); }
__device__ __forceinline__ void reg_fence(uint32_t (&d)[48]) {
#pragma unroll
  for (int i = 0; i < 48; i++) asm volatile("" : "+r"(d[i])::"memory");
}

constexpr uint32_t X_EXP = 17;
constexpr uint32_t X_LIM = ((15 + 8) << 7) - 1;
constexpr uint32_t U_LIM = ((15 + 6) << 10) - 1;
constexpr float W_MIN = 1.f / 8192;
constexpr uint32_t Y_MIN = 0x3C00, Y_INF = 0x7C00;
constexpr uint32_t NAN2 = 0x7FFF7FFFu;
using Sample = uint4;
__device__ __forceinline__ uint4 ldg128(const uint4* p) {
  uint4 v;
  asm volatile("ld.global.v4.u32 {%0,%1,%2,%3}, [%4];" : "=r"(v.x), "=r"(v.y), "=r"(v.z), "=r"(v.w) : "l"(p));
  return v;
}
__device__ __forceinline__ Sample sample_w(const __nv_bfloat16* w, int lane) {
  const int q = lane >> 3;
  return ldg128((const uint4*)(w + ((q == 0 ? 1 : q == 1 ? 3 : 4) * CH + 47 * q) * CH + 64 * (q % 3)) + (lane & 7));
}
__device__ __forceinline__ Sample sample_x(const __nv_bfloat16* x, int r, int lane) {
  return ldg128((const uint4*)(x + (size_t)(((r >> 3) * 8 + 1 + lane % 6) * IMG + (r & 7) * 64 + 2 * lane) * CH) + lane % 24);
}
__device__ __forceinline__ uint32_t sample_exp(const Sample& s) {
  const uint32_t m = __vmaxu2(__vimax3_u16x2(s.x & NAN2, s.y & NAN2, s.z & NAN2), s.w & NAN2);
  return __reduce_max_sync(0xffffffffu, max(m & 0xFFFFu, m >> 16)) >> 7;
}

constexpr int NP = 16, NTASK = NSUB * 36, NROUND = (NTASK + 8 * NP - 1) / (8 * NP), NSTAGE = 3;
__host__ __device__ constexpr int stage_end(int k) { return k == 0 ? 1 : k == 1 ? 3 : 2 * NROUND; }
__host__ __device__ constexpr int stage_first(int k) {
  for (int i = 0; i < NSTEP; i++)
    if (step_p(head(i)) / 4 * NROUND * 8 * NP + (step_n(head(i)) + 1) * 36 > stage_end(k - 1) * 8 * NP) return i;
  return -1;
}
static_assert(utrigger(stage_first(1)) >= 0 && stage_first(2) > stage_first(1), "stages");
struct Task {
  uint32_t n, s, kh, k;
  __device__ __forceinline__ Task(uint32_t t, int lane) {
    const uint32_t sub = t % 36;
    n = t / 36, s = sub / 12, kh = (sub / 6) & 1, k = sub % 6 * 32 + lane;
  }
};
constexpr int WTASK = 24 * 64;
__device__ __forceinline__ void prep_load(uint32_t dst, const __nv_bfloat16* __restrict__ w, uint32_t t, int lane) {
  const Task q(min(t, NTASK - 1), 0);
  w += ((q.s * 24 + 2 * q.n + q.kh) * 8 + (lane >> 2)) * CH + q.k + (lane & 3) * 8;
#pragma unroll
  for (int r = 0; r < 3; r++)
    asm volatile("cp.async.cg.shared.global [%0], [%1], 16;" ::"r"(dst + r * 512 + lane * 16), "l"(w + r * 3 * CH * CH) : "memory");
}
__device__ __forceinline__ void prep_store(const float (&g)[3][8], bool tiny, uint4* u, uint32_t t, bool h, int lane) {
  const Task q(t, lane);
  const uint32_t n = q.n, s = q.s, kh = q.kh, k = q.k;
  const uint32_t jn = (k >> 5) * 4 + ((k >> 1) & 3), row = ((k >> 3) & 3) * 2 + (k & 1);
  u += (((h ? 4 * NSUB : 0) + n) * USLAB + s * UTILE + jn * 256 + kh * 128 + row * 16) >> 4;
  constexpr float nA = -1.f / (2.f * A2 * DD), nB = 1.f / (2.f * B2 * DD);
  constexpr float f0 = nA / S1, f1 = nA / S2, f2 = nB / S3, f3 = nB / S4, f4 = 1.f / (A2 * B2);
  const float co[4][3] = {{h ? f4 : f0, h ? 0.f : PA * f0, h ? 0.f : A2 * f0},
                          {h ? 0.f : f1, h ? 0.f : -PA * f1, h ? 1.f : A2 * f1},
                          {f2, PB * f2, B2 * f2},
                          {f3, -PB * f3, B2 * f3}};
#pragma unroll
  for (int p = 0; p < 4; p++) {
    if (p == 2 && h) break;
    uint32_t o[4];
#pragma unroll
    for (int e = 0; e < 4; e++) {
      float v[2];
#pragma unroll
      for (int q = 0; q < 2; q++) v[q] = co[p][0] * g[0][2 * e + q] + co[p][1] * g[1][2 * e + q] + co[p][2] * g[2][2 * e + q];
      const uint32_t b = pack_bf16(v[0], v[1]);
      o[e] = pack_f16(__uint_as_float(b << 16), __uint_as_float(b & 0xFFFF0000u));
    }
    constexpr uint32_t lim = U_LIM * 0x10001u;
    if (__vimax3_u16x2(__vimax3_u16x2(lim, o[0] & NAN2, o[1] & NAN2), o[2] & NAN2, o[3] & NAN2) != lim || tiny) o[0] = NAN2;
    u[p * NSUB * USLAB / 16] = make_uint4(o[0], o[1], o[2], o[3]);
  }
}

constexpr int ROWB = IMG * CH * 2;

__device__ __forceinline__ int region_px(int r) { return (r >> 3) * 8 * IMG + (r & 7) * 64; }
__device__ __forceinline__ int halo_x(int r) { return (r & 7) * 64 - 1; }
__device__ __forceinline__ int halo_y(int r) { return (r >> 3) * 8 - 1; }

__device__ __noinline__ void direct_patch(const __nv_bfloat16* __restrict__ x, const __nv_bfloat16* __restrict__ w,
                                          __nv_bfloat16* __restrict__ out, int y0, int x0, int lane) {
  const int g = lane >> 2, t = lane & 3;
#pragma unroll 1
  for (int k0 = 0; k0 < CH; k0 += 48) {
    float acc[4][6][4] = {};
#pragma unroll 1
    for (int rs = 0; rs < 9; rs++) {
      const int iy = y0 + rs / 3 - 1, ix = x0 + rs % 3 - 1 + g;
#pragma unroll 2
      for (int c = 4 * t; c < CH; c += 16) {
        uint32_t b[6][2];
#pragma unroll
        for (int m = 0; m < 6; m++) {
          const uint32_t* p = (const uint32_t*)(w + (rs * CH + c + (m & 1) * 2) * CH + k0 + (m >> 1) * 16 + 2 * g);
          const uint32_t lo = p[0], hi = p[CH / 2];
          b[m & 6][m & 1] = __byte_perm(lo, hi, 0x5410);
          b[m | 1][m & 1] = __byte_perm(lo, hi, 0x7632);
        }
#pragma unroll
        for (int y = 0; y < 4; y++) {
          uint2 a[2];
#pragma unroll
          for (int h = 0; h < 2; h++)
            a[h] = (unsigned)(iy + y) < IMG && (unsigned)(ix + 8 * h) < IMG ? *(const uint2*)(x + ((iy + y) * IMG + ix + 8 * h) * CH + c)
                                                                           : make_uint2(0, 0);
#pragma unroll
          for (int m = 0; m < 6; m++)
            asm("mma.sync.aligned.m16n8k16.row.col.f32.bf16.bf16.f32 {%0,%1,%2,%3}, {%4,%5,%6,%7}, {%8,%9}, {%0,%1,%2,%3};"
                : "+f"(acc[y][m][0]), "+f"(acc[y][m][1]), "+f"(acc[y][m][2]), "+f"(acc[y][m][3])
                : "r"(a[0].x), "r"(a[1].x), "r"(a[0].y), "r"(a[1].y), "r"(b[m][0]), "r"(b[m][1]));
        }
      }
    }
#pragma unroll
    for (int y = 0; y < 4; y++)
#pragma unroll
      for (int m = 0; m < 6; m += 2)
#pragma unroll
        for (int h = 0; h < 2; h++)
          *(uint2*)(out + ((y0 + y) * IMG + x0 + g + 8 * h) * CH + k0 + m * 8 + 4 * t) =
              make_uint2(pack_bf16(acc[y][m][2 * h], acc[y][m + 1][2 * h]), pack_bf16(acc[y][m][2 * h + 1], acc[y][m + 1][2 * h + 1]));
  }
}

struct Descs { uint64_t a[2][6], b[22]; };
__host__ __device__ constexpr int slot_use(int i) {
  int c = 0;
  for (int j = 0; j < i; j++) c += vslot(step_p(j), step_n(j)) == vslot(step_p(i), step_n(i));
  return c;
}

__host__ __device__ constexpr int out_time(int q) {
  constexpr int t[24] = {
      49, 50, 51, 52, 54, 55, 56, 57, 59, 60, 61, 63, 64, 65, 66, 68, 69, 70, 72, 74, 76, 78, 80, 82};
  return t[q];
}
__host__ __device__ constexpr int out_at(int t) {
  for (int q = 0; q < 24; q++)
    if (out_time(q) % NSTEP == t) return q;
  return -1;
}
__host__ __device__ constexpr bool out_ok() {
  for (int q = 0; q < 24; q++)
    if (out_time(q) <= last_on(q / 6) || out_time(q) < PIV + (q < 12 ? 4 : 6) || out_time(q) >= first_on(q / 6) + NSTEP ||
        (q && out_time(q) <= out_time(q - 1)))
      return false;
  return true;
}
static_assert(out_ok(), "output plan");
constexpr int OUT_END = out_time(23) + 1 - NSTEP;

struct Consumer {
  uint32_t c1[48], c2[48], c3[48], c4[48];
  const uint64_t *descA, *descB;
  static constexpr uint32_t sb = SMEM_BASE;
  uint8_t* pout;
  int bid, nblk, nlong;
  uint32_t done;
  uint32_t osc, ymax[2];
  bool lead, ok, odd;

  uint32_t one;
  __device__ __forceinline__ bool always() {
    uint32_t v = one;
    asm volatile("" : "+r"(v));
    return v != 0;
  }
  __device__ __forceinline__ void axpy(uint32_t (&a)[48], uint32_t k, uint32_t (&b)[48]) {
    if (always()) {
      reg_fence(a); reg_fence(b);
#pragma unroll
      for (int i = 0; i < 48; i++) {
        a[i] = hfma2(k, b[i], a[i]);
        if (i % 12 == 11) {
          asm volatile("" : "+r"(a[i])::"memory");
          sched_barrier();
        }
      }
      reg_fence(a);
    }
  }
  uint32_t pa[4], pb[4], px[4];
  __device__ __forceinline__ uint32_t to_bf16(uint32_t h, uint32_t& m) {
    float lo, hi;
    asm("{\n.reg .b16 l, h;\n.reg .b32 m;\nmov.b32 {l, h}, %3;\ncvt.f32.f16 %0, l;\ncvt.f32.f16 %1, h;\n"
        "abs.f16x2 m, %3;\nmax.NaN.f16x2 %2, m, %2;\n}\n" : "=f"(lo), "=f"(hi), "+r"(m) : "r"(h));
    return bmul2(pack_bf16(lo, hi), osc);
  }
  template <int Q, int EXTRA>
  __device__ __forceinline__ void stg(const uint32_t (&v)[4]) {
    constexpr int y = Q < 6 ? 1 : Q < 12 ? 2 : Q < 18 ? 0 : 3;
    asm volatile("st.global.cs.v4.u32 [%0+%5], {%1,%2,%3,%4};" ::"l"(pout), "r"(v[0]), "r"(v[1]), "r"(v[2]), "r"(v[3]),
                 "n"(y * ROWB + (Q / 3) % 2 * 8 * (CH * 2) + Q % 3 * 128 + EXTRA) : "memory");
  }
  template <int Q, bool YIELD>
  __device__ __forceinline__ void convert(uint32_t (&a)[4], uint32_t (&b)[4], uint32_t (&send)[4]) {
    if constexpr (Q >= 0) {
      const uint32_t(&d)[48] = Q < 6 ? c1 : Q < 12 ? c2 : Q < 18 ? c3 : c4;
      constexpr int o = 16 * (Q % 3) + (Q / 3) % 2;
#pragma unroll
      for (int e = 0; e < 4; e++) {
        if (YIELD && e % 2 == 0) sched_barrier();
        a[e] = to_bf16(d[o + 2 * e], ymax[o & 1]);
        b[e] = to_bf16(d[o + 8 + 2 * e], ymax[o & 1]);
        send[e] = odd ? a[e] : b[e];
      }
    }
  }
  template <int QW, int QR, bool STEP>
  __device__ __forceinline__ void output() {
    uint32_t u[4], v[4], a[4], b[4], send[4];
    if constexpr (!STEP) convert<QR, false>(a, b, send);
    sched_barrier();
#pragma unroll
    for (int e = 0; e < 4; e++) {
      u[e] = odd ? px[e] : pa[e];
      v[e] = odd ? pb[e] : px[e];
    }
    if constexpr (STEP) {
      convert<QR, true>(a, b, send);
      asm volatile("{\n.reg .pred p;\nsetp.ne.u32 p, %0, 0;\n@p pmevent 0;\n}" ::"r"((uint32_t)ok) : "memory");
      sched_barrier();
    }
    if constexpr (QW >= 0 && STEP) { stg<QW, 0>(u); stg<QW, CH * 2>(v); }
    if constexpr (QR >= 0) {
#pragma unroll
      for (int e = 0; e < 4; e++) px[e] = __shfl_xor_sync(0xffffffffu, send[e], 4), pa[e] = a[e], pb[e] = b[e];
    }
    if constexpr (QW >= 0 && !STEP) { stg<QW, 0>(u); stg<QW, CH * 2>(v); }
    sched_barrier();
  }
  __device__ __forceinline__ void range_check() {
    sched_barrier();
    uint32_t m = __vmaxu2(__byte_perm(ymax[0], ymax[1], 0x5410), __byte_perm(ymax[0], ymax[1], 0x7632));
    m = __vmaxu2(m, __shfl_xor_sync(0xffffffffu, m, 1));
    m = __vmaxu2(m, __shfl_xor_sync(0xffffffffu, m, 2));
    asm volatile("{\n.reg .pred p;\nsetp.ge.u32 p, %2, %3;\n@p st.shared.u8 [%0], %1;\n}" ::"r"(sb + OFF_REDO + (threadIdx.x & ~31u) + done), "r"(1),
                 "r"(max((m & 0xFFFFu) - Y_MIN, (m >> 16) - Y_MIN)), "n"(Y_INF - Y_MIN) : "memory");
    ymax[0] = ymax[1] = 0;
  }
  template <int T, int Q0, int Q1, int Q = Q0>
  __device__ __forceinline__ void flush() {
    if constexpr (Q <= Q1) {
      constexpr int QW = Q > Q0 && out_time((Q + 23) % 24) >= T - 1 ? Q - 1 : -1, QR = Q < Q1 && out_time(Q % 24) >= T ? Q : -1;
      if constexpr (QW >= 0 || QR >= 0) output<QW, QR, false>();
      flush<T, Q0, Q1, Q + 1>();
    }
  }
  template <int I>
  __device__ __forceinline__ void hook() {
    constexpr float LP = PB * (PB - PA) / (2.f * A2), LM = PB * (PB + PA) / (2.f * A2);
    constexpr int QW = out_at((I + NSTEP - 1) % NSTEP), QR = out_at(I);
    if constexpr (QW >= 0 || QR >= 0) output<QW, QR, true>();
    if constexpr (I == 22) {
      static_assert(OUT_END < NHEAD, "pointer update");
      range_check();
      osc = lds32(sb + OFF_OSC);
      const int r = bid + done * nblk, d = region_px(r) - region_px(r - nblk);
      asm volatile("mad.wide.s32 %0, %1, 384, %0;" : "+l"(pout) : "r"(d));
    }
    if constexpr (I == NHEAD) { if (bid >= nlong && done == 0 && !(bid & 3)) spin_cycles(24500); }
    if constexpr (I == 42) { if (bid >= nlong && done == 0 && (bid & 3)) spin_cycles(28000); }
    if constexpr (I == PIV) axpy(c1, h2const(S3 * (B2 / A2) / S1), c3);
    if constexpr (I == PIV) axpy(c2, h2const(S3 * (B2 / A2) / S2), c3);
    if constexpr (I == PIV + 1) axpy(c4, h2const(-S3 / S4), c3);
    if constexpr (I == PIV + 1) axpy(c1, h2const(S4 * LP / S1), c4);
    if constexpr (I == PIV + 2) axpy(c2, h2const(S4 * LM / S2), c4);
    if constexpr (I == PIV + 2) axpy(c3, h2const(S4 * (-DD / A2)), c4);
    if constexpr (I == PIV + 3) { axpy(c1, h2const(-1.f / (2.f * PA)), c2); axpy(c2, h2const(PA), c1); }
    if constexpr (I == PIV + 4) axpy(c4, h2const(A2), c1);
    if constexpr (I == PIV + 5) axpy(c3, h2const(1.f / A2), c2);
  }

  template <int I, int END, bool FIRST = false>
  __device__ __forceinline__ void steps() {
    if constexpr (I < END) {
      constexpr int J = (I + 1) % NSTEP, S = FIRST ? head(I) : I, T = FIRST ? head(J) : J, G = FIRST ? head_gate_of(I) : gate_of(I);
      uint32_t(&d)[48] = step_acc(S) == 0 ? c1 : step_acc(S) == 1 ? c2 : step_acc(S) == 2 ? c3 : c4;
      constexpr int vo = vslot(step_p(S), step_n(S)) * VSLOT, uo = USLOT<I> * USLAB;
      if (!ok) {
        mbar_wait_short(sb + BAR_UFULL + 8 * USLOT<I>, UUSE<I> & 1);
        if constexpr (first_use(step_n(S)) == S) mbar_wait_short(sb + BAR_VFULL + 8 * (step_n(S) % NB), step_n(S) / NB);
      }
      const uint64_t da = descA[FIRST ? 4 : slot_use(I)], db = descB[(FIRST ? 16 : 0) + UUSE<I>];
      wg_fence();
      wgmma192<vo, uo>(d, da, db, first_on(step_acc(S)) == S ? 0u : 1u);
      wgmma192<vo + 16, uo + UTILE>(d, da, db, 1u);
      wgmma192<vo + 32, uo + 2 * UTILE>(d, da, db, 1u);
      wg_commit();
      ok = mbar_test(sb + BAR_UFULL + 8 * USLOT<J>, UUSE<J> & 1);
      if constexpr (first_use(step_n(T)) == T) ok &= mbar_test(sb + BAR_VFULL + 8 * (step_n(T) % NB), step_n(T) / NB);
      if constexpr (!FIRST) hook<I>();
      wg_wait<0>();
      reg_fence(d);
      if (lead) mbar_arrive(sb + BAR_UEMPTY + 8 * USLOT<I>);
      if constexpr (G >= 0) { if (lead) mbar_arrive(sb + BAR_GATE + 8 * (G % NB)); }
      steps<I + 1, END, FIRST>();
    }
  }
  template <int I>
  __device__ __forceinline__ void chain() {
    if constexpr (I < NSTEP) {
      static_assert(step_acc(I) == 3 && NSTEP - I <= NU, "chain");
      constexpr int vo = vslot(step_p(I), step_n(I)) * VSLOT, uo = USLOT<I> * USLAB;
      mbar_wait_short(sb + BAR_UFULL + 8 * USLOT<I>, UUSE<I> & 1);
      const uint64_t da = descA[5], db = descB[21];
      wg_fence();
      wgmma192<vo, uo>(c4, da, db, 1u);
      wgmma192<vo + 16, uo + UTILE>(c4, da, db, 1u);
      wgmma192<vo + 32, uo + 2 * UTILE>(c4, da, db, 1u);
      wg_commit();
      chain<I + 1>();
    }
  }
  template <int I>
  __device__ __forceinline__ void release() {
    if constexpr (I < NSTEP) {
      if (lead) mbar_arrive(sb + BAR_UEMPTY + 8 * USLOT<I>);
      release<I + 1>();
    }
  }
  template <int T>
  __device__ __forceinline__ void finish(bool second) {
    if (second) {
      flush<T, 0, 18>();
      asm volatile("bar.sync 1, 256;" ::: "memory");
    }
    chain<T>();
    if (!second) {
      asm volatile("bar.arrive 1, 256;" ::: "memory");
      flush<T, 0, 18>();
    }
    wg_wait<0>();
    reg_fence(c4);
    release<T>();
    done++;
    flush<T, 18, 24>();
  }
};

struct SlotTab { uint32_t off[NSUB][8]; };
constexpr SlotTab make_slots() {
  SlotTab t = {};
  for (int n = 0; n < NSUB; n++)
    for (int p = 0; p < 6; p++) t.off[n][p] = vslot(p, n) * VSLOT;
  return t;
}
__constant__ __align__(64) SlotTab c_slots = make_slots();

constexpr int PF_X = 22, PF_NB = 12, U_LEAD = 9;
__host__ __device__ constexpr uint32_t pf_box(int k) { return 1u << 31 | (k / PF_NB / 3) << 30 | (k / PF_NB % 3) << 28 | (k % PF_NB) << 24; }
__host__ __device__ constexpr int slab_of(int i) { return step_p(i % NSTEP) * NSUB + step_n(i % NSTEP); }
struct LoadTab { uint32_t e[2 * NSTEP]; };
constexpr LoadTab make_loads() {
  LoadTab t = {};
  constexpr int win[6] = {25, 42, 45, 72, 73, 96};
  for (int k = 0, i = 0; k < 6 * PF_NB; k++) {
    const int g = k / PF_NB % 3, when = win[2 * g] + k % PF_NB * (win[2 * g + 1] - win[2 * g]) / PF_NB - (k < 3 * PF_NB ? NSTEP : 0);
    if (when >= 0 && when < NSTEP) t.e[NSTEP + when] = pf_box(k);
    if (k < PF_NB) continue;
    if (i < when) i = when;
    if (i < NSTEP) t.e[i++] = pf_box(k);
  }
  for (int i = 0; i < 2 * NSTEP; i++) {
    int d = 1;
    while (uslot((i + d) % NSTEP) != uslot(i % NSTEP)) d++;
    if (d > NU + 1) d = 0;
    t.e[i] |= (uuse(i % NSTEP) & 1) << 23 | uslot(i % NSTEP) << 20 | d << 16 | slab_of(i + U_LEAD) << 8 | slab_of(head(i + d));
  }
  return t;
}
__constant__ __align__(64) LoadTab c_load = make_loads();

template <int I>
__device__ __forceinline__ void first_slabs(const uint8_t* u) {
  if constexpr (utrigger(I) < 0) {
    constexpr int slab = slab_of(head(I));
    load_u_warp(SMEM_BASE + OFF_U + USLOT<I> * USLAB, u + slab * USLAB, SMEM_BASE + BAR_UFULL + 8 * USLOT<I>);
    first_slabs<I + 1>(u);
  }
}

template <int BYTES>
__device__ __forceinline__ uint32_t warm(const void* p, uint32_t zero) {
  uint32_t v = ~0u;
#pragma unroll
  for (int o = 0; o < BYTES; o += 64) v &= ((const uint32_t*)p)[o / 4 + zero];
  return v;
}

__global__ void __launch_bounds__(384, 1) __cluster_dims__(1, 1, 1)
conv_kernel(const __nv_bfloat16* __restrict__ xin, const __nv_bfloat16* __restrict__ wgt, __nv_bfloat16* __restrict__ out, Scratch* scratch,
            int nblk, int nlong, int nmax,
            const __grid_constant__ CUtensorMap tmX, const __grid_constant__ CUtensorMap tmH, const __grid_constant__ CUtensorMap tmP,
            const __grid_constant__ Descs desc) {
  uint4* const ubuf = scratch->u;
  uint32_t* const arrived = scratch->arrived;
  extern __shared__ uint8_t smem_raw[];
  const int tid = threadIdx.x, lane = tid & 31, bid = blockIdx.x;
  const int pidx = bid - (nblk - NP);
  constexpr uint32_t sb = SMEM_BASE;
  uint32_t epoch = 0;
  if (tid < 256) {
    cluster_arrive_relaxed();
    if (pidx >= 0) {
      const uint32_t t0 = pidx * 8 + (tid >> 5), wsm = sb + OFF_V + (tid >> 5) * NROUND * WTASK;
      prep_load(wsm, wgt, t0, lane);
      const Sample ws = sample_w(wgt, lane);
      sched_barrier();
      const float sw = __uint_as_float(max(253 - (int)sample_exp(ws), 0) << 23);
      const int klane = (lane & 6) * 4 + (lane >> 3) * 2 + (lane & 1);
      int stage = 0;
#pragma unroll 1
      for (int round = 0; round < 2 * NROUND; round++) {
        const int k = round < NROUND ? round : round - NROUND;
        asm volatile("cp.async.wait_all;" ::: "memory");
        __syncwarp();
        float g[3][8], gmax = 0.f;
#pragma unroll
        for (int i = 0; i < 24; i++) {
          uint16_t v;
          asm volatile("ld.shared.u16 %0, [%1];" : "=h"(v) : "r"(wsm + k * WTASK + i * 64 + klane * 2) : "memory");
          g[i / 8][i % 8] = __uint_as_float((uint32_t)v << 16);
        }
        if (round >= NROUND) {
#pragma unroll
          for (int i = 0; i < 24; i++) gmax = fmaxf(gmax, fabsf(g[i / 8][i % 8]));
          sched_barrier();
        }
#pragma unroll
        for (int i = 0; i < 24; i++) g[i / 8][i % 8] *= sw;
        if (t0 + k * 8 * NP < NTASK) prep_store(g, gmax > 0.f && gmax * sw < W_MIN, ubuf, t0 + k * 8 * NP, round >= NROUND, klane);
        if (round + 1 == stage_end(0) || round + 1 == stage_end(1) || round + 1 == stage_end(2)) {
          if (++stage == NSTAGE) {
            fence_async();
            asm volatile("ld.relaxed.gpu.global.u32 %0, [%1];" : "=r"(epoch) : "l"(arrived + 32 * NSTAGE) : "memory");
          }
          asm volatile("bar.sync 1, 256;" ::: "memory");
          if (tid == 0)
            asm volatile("red.release.gpu.global.add.u32 [%0], %1;" ::"l"(arrived + 32 * stage), "r"(pidx ? 1 : 0x80000001u - NP) : "memory");
          asm volatile("bar.sync 1, 256;" ::: "memory");
          if (stage == 1) {
#pragma unroll 1
            for (int j = 1; j < NROUND; j++) prep_load(wsm + j * WTASK, wgt, t0 + j * 8 * NP, lane);
          }
        }
      }
      if (tid < 32) asm volatile("bar.arrive 2, 64;" ::: "memory");
    } else if (tid < 32) {
      epoch = stage_enter(arrived, lane, 1);
      spin_until(now(), 2200);
    }
  }
  if (tid >= 352) {
    asm volatile("prefetch.tensormap [%0];" ::"l"(&tmX) : "memory");
    constexpr uint64_t twos = ((2ull << NU) - 1) << (BAR_UEMPTY - OFF_BAR) / 8 | ((1ull << 2 * NB) - 1) << (BAR_VFULL - OFF_BAR) / 8;
    constexpr uint64_t threes = ((1ull << NB) - 1) << (BAR_VFULL - OFF_BAR) / 8;
    if (lane == 0) {
#pragma unroll
      for (int i = 0; i < NBAR; i++) mbar_init(sb + OFF_BAR + 8 * i, 1 + ((twos >> i) & 1) + ((threes >> i) & 1));
      asm volatile("fence.mbarrier_init.release.cluster;" ::: "memory");
      fence_async();
    }
    __syncwarp();
    cluster_arrive_relaxed();
    epoch = stage_enter(arrived, lane, pidx ? 1 : 0x80000001u + NP - 2 * nblk);
    if (pidx >= 0) asm volatile("bar.sync 2, 64;" ::: "memory");
    const uint32_t t0 = now();
#pragma unroll 1
    for (int k = 0, box = 0; k < 9; k++, box = box < 6 ? box + 3 : box - 5) {
      if (pidx < 0) spin_until(t0, min(k, 7) * 410);
      tma_box_warp(sb + OFF_X + box * XBOX, k < 8 ? &tmX : &tmH, sb + BAR_XFULL + 8 * box, k < 8 ? XBOX : XHBOX, 0, halo_x(bid) + k * 8,
                   halo_y(bid));
      if (k == 0) asm volatile("prefetch.tensormap [%0];\nprefetch.tensormap [%1];" ::"l"(&tmH), "l"(&tmP) : "memory");
    }
  }
  if (smem_u32(smem_raw) != SMEM_BASE) __trap();
  const int warp = __shfl_sync(0xffffffffu, tid >> 5, 0);

  if (warp < 8) {
    const int wg = warp >> 2;
    if (warp == 7) {
      spin_until(now(), 1300);
      if ((warm<sizeof(SlotTab)>(&c_slots, tid >> 10) & warm<sizeof(LoadTab)>(&c_load, tid >> 10) & warm<sizeof(Descs)>(&desc, tid >> 10)) == ~0u)
        __trap();
    }
    cluster_wait();
    if (warp == 0) {
      stage_wait(arrived + 32, __shfl_sync(0xffffffffu, epoch, 0));
      first_slabs<0>((const uint8_t*)ubuf);
    }
    asm volatile("setmaxnreg.inc.sync.aligned.u32 224;");
    Consumer c;
#pragma unroll
    for (int i = 0; i < 48; i++) { c.c1[i] = 0; c.c2[i] = 0; c.c3[i] = 0; c.c4[i] = 0; }
#pragma unroll
    for (int e = 0; e < 4; e++) c.pa[e] = c.pb[e] = c.px[e] = 0;
    c.descA = desc.a[wg];
    c.descB = desc.b;
    c.lead = (tid & 127) == 0;
    c.one = __shfl_sync(0xffffffffu, nblk, 0);
    c.ok = false;
    c.bid = bid;
    c.nblk = nblk;
    c.nlong = nlong;
    c.odd = (lane >> 2) & 1;
    c.pout = (uint8_t*)out + (long long)(region_px(bid - nblk) + wg * 4 * IMG + (warp & 3) * 16 + (lane >> 3) * 2) * (CH * 2) + (lane & 7) * 16;
    c.done = c.osc = c.ymax[0] = c.ymax[1] = 0;
    asm volatile("st.shared.u8 [%0], %1;" ::"r"(sb + OFF_REDO + tid), "r"(0) : "memory");
    constexpr int ROT = 69;
    c.steps<0, NHEAD, true>();
    bool tail = false;
#pragma unroll 1
    do {
      wg_wait<0>();
      if (tail) {
        c.steps<ROT, NSTEP>();
        c.done++;
        c.steps<0, NHEAD>();
      }
      c.steps<NHEAD, ROT>();
      tail = c.always();
    } while (bid + (int)(c.done + 1) * nblk < NREG);
    c.finish<ROT>(wg);
    c.range_check();
    __syncwarp();
    uint32_t redo;
    asm volatile("ld.shared.u8 %0, [%1];" : "=r"(redo) : "r"(sb + OFF_REDO + tid) : "memory");
    redo = __ballot_sync(0xffffffffu, redo) >> 1;
    if (redo) {
      for (int i = 0; i < (int)c.done; i++)
        if ((redo >> i) & 1) {
          const int r = bid + i * nblk;
          direct_patch(xin, wgt, out, (r >> 3) * 8 + wg * 4, (r & 7) * 64 + (warp & 3) * 16, lane);
        }
    }
  } else {
    asm volatile("setmaxnreg.dec.sync.aligned.u32 56;");
    const int nitem = nmax - (bid >= nlong);
    if (warp == 11) {
      const uint8_t* ubase = (const uint8_t*)ubuf;
      epoch = __shfl_sync(0xffffffffu, epoch, 0);
      cluster_wait();
      const uint8_t* uline = ubase + (bid * 2 + lane) * 128;
      const bool ufetch = lane < 2 && bid < USLAB / 256;
      int r = bid, i = 0, tab = 0;
#pragma unroll 1
      for (int left = nitem * NSTEP - 1; left >= 0; left--) {
        const uint32_t e = c_load.e[tab + i], slot = (e >> 20) & 7;
        const uint8_t* src = ubase + (e & 255) * USLAB;
        const uint8_t* pu = uline + ((e >> 8) & 255) * USLAB;
        const uint32_t dst = sb + OFF_U + slot * USLAB, ebar = sb + BAR_UEMPTY + 8 * slot;
        const bool refill = ((e >> 16) & 7) - 1 < (uint32_t)left;
        constexpr int need1 = utrigger(stage_first(1)), need2 = utrigger(stage_first(2)), xslab = slab_of(UX_FIRST);
        if (tab + i == need1 || tab + i == need2) stage_wait(arrived + (i == need1 ? 64 : 96), epoch);
        refill_u(ebar, (e >> 23) & 1, refill, dst, src);
        if (i == UX_GATE) load_u_warp(sb + OFF_V, ubase + xslab * USLAB, sb + BAR_UFULL + 8 * NU);
        const int rr = r + ((e >> 30) & 1) * nblk;
        if ((int)e < 0 && rr < NREG)
          asm volatile("{\n.reg .pred p;\nelect.sync _|p, 0xffffffff;\n"
                       "@p cp.async.bulk.prefetch.tensor.3d.L2.global.tile [%0, {%1, %2, %3}];\n}\n" ::"l"(&tmP), "r"((e >> 22) & 0xC0),
                       "r"(halo_x(rr) + ((e >> 26) & 3) * PF_X), "r"(halo_y(rr) + 1 + ((e >> 23) & 6)) : "memory");
        if (ufetch && tab + i >= NSTEP - U_LEAD && left >= U_LEAD) asm volatile("prefetch.global.L2 [%0];" ::"l"(pu) : "memory");
        if (++i == NSTEP) { i = 0; r += nblk; tab = NSTEP; }
      }
    } else {
      cluster_arrive_relaxed();
      const int w = warp - 8, col = (lane >> 1) & 7, chunk = lane >> 4;
      const uint32_t xbox = sb + OFF_X + w * 3 * XBOX, xbar = sb + BAR_XFULL + 24 * w;
      const uint32_t xl = xbox + col * 32 + ((chunk ^ (col >> 2)) << 4) + (lane & 1) * 8;
      const uint32_t vl = sb + OFF_V + chunk * VROW + w * 128 + (lane & 15) * 8;
      const bool in_row = w < 2 || col < 2;
      const uint32_t pitch2 = w < 2 ? 256 : 64, bytes2 = 10 * pitch2;
      const uint32_t xl2 = w < 2 ? xl + 2 * XBOX : xbox + 2 * XBOX + col * 32 + chunk * 16 + (lane & 1) * 8;
      const CUtensorMap* tm2 = w < 2 ? &tmX : &tmH;
      auto xrow = [&](int j, int i) {
        uint2 v = make_uint2(0, 0);
        if (j < 2 || in_row) v = lds64(j < 2 ? xl + j * XBOX + i * 256 : xl2 + i * pitch2);
        return v;
      };
      const Sample ws = sample_w(wgt, lane), xs = sample_x(xin, bid, lane);
      uint32_t xsc;
      {
        const int ex = sample_exp(xs), eo = ex + (int)sample_exp(ws) - (111 + X_EXP), es = 127 + X_EXP - ex;
        xsc = es >= 1 && eo >= 1 && eo <= 254 ? es * 0x00800080u : NAN2;
        asm volatile("st.shared.u32 [%0], %1;" ::"r"(sb + OFF_OSC), "r"(eo * 0x00800080u) : "memory");
      }
      constexpr uint32_t gate_par = [] {
        uint32_t m = 0;
        for (int n = 0; n < NSUB; n++) m |= (uint32_t)((n / NB) ^ (gate(n % NB) < 0)) << n;
        return m;
      }();
      constexpr uint32_t LIM2 = X_LIM * 0x10001u;
      cluster_wait();
      auto conv = [&](uint2& v, uint32_t m) {
        const uint32_t tx = bmul2(v.x, xsc), ty = bmul2(v.y, xsc), ux = tx & NAN2, uy = ty & NAN2;
        v = make_uint2(ux * 7 + tx, uy * 7 + ty);
        return __vimax3_u16x2(m, ux, uy);
      };
      uint32_t so[6] = {};
      auto planes = [&](const uint2* h, uint32_t m, uint32_t a, bool on) {
        constexpr uint32_t NB2 = h2const(-B2), NA2 = h2const(-A2);
        const uint2 e1 = fma4(NB2, h[2], h[4]), e2 = fma4(NA2, h[2], h[4]);
        store_v(a + so[4], fma4(NA2, fma4(NB2, h[0], h[2]), e1), on);
        const uint2 o1 = fma4(NB2, h[1], h[3]), o2 = fma4(NA2, h[1], h[3]);
        store_v(a + so[5], fma4(NA2, o1, fma4(NB2, h[3], h[5])), on);
        uint2 v = fma4(h2const(PA), o1, e1);
        if (m != LIM2) v.x = NAN2;
        store_v(a + so[0], v, on);
        store_v(a + so[1], fma4(h2const(-PA), o1, e1), on);
        store_v(a + so[2], fma4(h2const(PB), o2, e2), on);
        store_v(a + so[3], fma4(h2const(-PB), o2, e2), on);
      };
      int r = bid, n = 0;
      uint32_t par = 0;
#pragma unroll 1
      for (int left = nitem * NSUB; left > 0; left--) {
        const int nb = n >= NB ? n - NB : n;
        uint2 d[10];
        mbar_wait(xbar, par);
#pragma unroll
        for (int i = 0; i < 6; i++) d[i] = xrow(0, i);
#pragma unroll
        for (int p = 0; p < 6; p++) so[p] = c_slots.off[n][p];
        const uint32_t gpar = (gate_par >> n) & 1;
        if (++n == NSUB) { n = 0; r += nblk; }
        const int fc = n * 16, fx = halo_x(r) + w * 8, fy = halo_y(r);
#pragma unroll
        for (int j = 0; j < 3; j++) {
          const bool on = j < 2 || in_row;
#pragma unroll
          for (int i = 6; i < 10; i++) d[i] = xrow(j, i);
          const bool xok = j < 2 && mbar_test(xbar + 8 * (j + 1), par);
          sched_barrier();
          const uint32_t m45 = conv(d[5], conv(d[4], LIM2));
          const uint32_t ma = conv(d[3], conv(d[1], conv(d[0], conv(d[2], m45))));
          if (j == 0) mbar_wait(sb + BAR_GATE + 8 * nb, gpar);
          planes(d, ma, vl + j * 384, on);
          sched_barrier();
          const uint32_t mb = conv(d[9], conv(d[7], conv(d[6], conv(d[8], m45))));
          if (left > 1)
            tma_box_warp(xbox + j * XBOX, j < 2 ? &tmX : tm2, xbar + 8 * j, (j < 2 ? XBOX : bytes2) | (mb & 0x8000u), fc, fx + j * 24, fy);
          uint2 h[6];
#pragma unroll
          for (int i = 0; i < 6; i++) h[i] = d[4 + i];
          if (j < 2) {
            mbar_wait(xbar + 8 * (j + 1), par, xok);
#pragma unroll
            for (int i = 0; i < 6; i++) d[i] = xrow(j + 1, i);
          }
          sched_barrier();
          planes(h, mb, vl + j * 384 + VPIECE, on);
          sched_barrier();
        }
        fence_async();
        asm volatile("{\n.reg .pred p;\nelect.sync _|p, 0xffffffff;\n@p mbarrier.arrive.shared::cta.b64 _, [%0];\n}\n"
                     ::"r"(sb + BAR_VFULL + 8 * nb) : "memory");
        par ^= 1;
      }
    }
  }
}

constexpr uint64_t make_desc(uint32_t off, uint32_t lbo, uint32_t sbo) {
  return (uint64_t)((SMEM_BASE + off) >> 4) | ((uint64_t)(lbo >> 4) << 16) | ((uint64_t)(sbo >> 4) << 32);
}

typedef CUresult (*EncodeFn)(CUtensorMap*, CUtensorMapDataType, cuuint32_t, void*, const cuuint64_t*, const cuuint64_t*,
                             const cuuint32_t*, const cuuint32_t*, CUtensorMapInterleave, CUtensorMapSwizzle,
                             CUtensorMapL2promotion, CUtensorMapFloatOOBfill);

}

extern "C" void kernel_launch(void* const* d_in, const int* in_sizes, int n_in, void* d_out, int out_size) {
  static EncodeFn enc = nullptr;
  static int nblk = 0;
  static Scratch* scratch;
  if (!enc) {
    cudaGetSymbolAddress((void**)&scratch, g_scratch);
    cudaDriverEntryPointQueryResult qr;
    cudaGetDriverEntryPoint("cuTensorMapEncodeTiled", (void**)&enc, cudaEnableDefault, &qr);
    cudaFuncSetAttribute(conv_kernel, cudaFuncAttributeMaxDynamicSharedMemorySize, SMEM_BYTES);
    int dev;
    cudaGetDevice(&dev);
    cudaDeviceGetAttribute(&nblk, cudaDevAttrMultiProcessorCount, dev);
  }
  CUtensorMap tmX, tmH, tmP;
  const cuuint64_t dims[3] = {CH, IMG, IMG};
  const cuuint64_t strides[2] = {CH * 2, (cuuint64_t)CH * 2 * IMG};
  const cuuint32_t es[3] = {1, 1, 1};
  const cuuint32_t boxX[3] = {16, 8, 10}, boxH[3] = {16, 2, 10}, boxP[3] = {64, PF_X, 2};
  enc(&tmH, CU_TENSOR_MAP_DATA_TYPE_BFLOAT16, 3, d_in[0], dims, strides, boxH, es, CU_TENSOR_MAP_INTERLEAVE_NONE,
      CU_TENSOR_MAP_SWIZZLE_NONE, CU_TENSOR_MAP_L2_PROMOTION_L2_64B, CU_TENSOR_MAP_FLOAT_OOB_FILL_NONE);
  enc(&tmP, CU_TENSOR_MAP_DATA_TYPE_BFLOAT16, 3, d_in[0], dims, strides, boxP, es, CU_TENSOR_MAP_INTERLEAVE_NONE,
      CU_TENSOR_MAP_SWIZZLE_NONE, CU_TENSOR_MAP_L2_PROMOTION_L2_128B, CU_TENSOR_MAP_FLOAT_OOB_FILL_NONE);
  enc(&tmX, CU_TENSOR_MAP_DATA_TYPE_BFLOAT16, 3, d_in[0], dims, strides, boxX, es, CU_TENSOR_MAP_INTERLEAVE_NONE,
      CU_TENSOR_MAP_SWIZZLE_32B, CU_TENSOR_MAP_L2_PROMOTION_L2_64B, CU_TENSOR_MAP_FLOAT_OOB_FILL_NONE);
  Descs desc = {};
  for (int i = 0; i < 6; i++) { desc.a[0][i] = make_desc(OFF_V, VROW, 128); desc.a[1][i] = make_desc(OFF_V + VPIECE, VROW, 128); }
  for (int i = 0; i < 22; i++) desc.b[i] = make_desc(OFF_U, 128, 256);
  conv_kernel<<<nblk, 384, SMEM_BYTES>>>((const __nv_bfloat16*)d_in[0], (const __nv_bfloat16*)d_in[1], (__nv_bfloat16*)d_out, scratch, nblk,
                                         NREG % nblk ? NREG % nblk : nblk, (NREG + nblk - 1) / nblk, tmX, tmH, tmP, desc);
}
```
